```python
import torch

def _softmax(x, axis=-1):
    return torch.softmax(x, dim=axis)

def _gelu(x):
    return torch.nn.functional.gelu(x, approximate='tanh')

def _silu(x):
    return torch.nn.functional.silu(x)

def _sigmoid(x):
    return torch.sigmoid(x)

def _layernorm(x, axis=-1, eps=1e-05):
    m = x.mean(dim=axis, keepdim=True)
    v = x.var(dim=axis, keepdim=True, unbiased=False)
    return (x - m) / torch.sqrt(v + eps)

def _scatter_add(tgt, idx, src, axis=0):
    return tgt.clone().index_add_(axis, idx, src)

def _segment_sum(src, seg, n):
    out = torch.zeros((n,) + src.shape[1:], dtype=src.dtype)
    return out.index_add_(0, seg, src)

def _pad(x, pw):
    flat = tuple((v for pair in reversed(pw) for v in pair))
    return torch.nn.functional.pad(x, flat)
kernel_name = 'concat_heads__memory_aug_recurrent_mem_tr__linear_attn_block__prompt'

def setup_inputs():

    _w = lambda a: (lambda t: t.to(torch.bfloat16) if t.is_floating_point() else t)(torch.as_tensor(a))

    def _A_setup():
        B, S, Dm = (1, 2048, 448)
        H, Dh = (16, 256)
        M, seg = (8, 32)
        seg = min(seg, S)
        S = S // seg * seg
        return {'x': _w((lambda *s: torch.randn(*s, dtype=torch.bfloat16) * 0.05)(B, S, Dm)), 'mem0': _w((lambda *s: torch.randn(*s, dtype=torch.bfloat16) * 0.8)(B, M, Dm)), 'Wq': _w((lambda *s: torch.randn(*s, dtype=torch.bfloat16) * 1.6)(Dm, H, Dh) * Dm ** (-0.5)), 'Wk': _w((lambda *s: torch.randn(*s, dtype=torch.bfloat16) * 1.6)(Dm, H, Dh) * Dm ** (-0.5)), 'Wv': _w((lambda *s: torch.randn(*s, dtype=torch.bfloat16) * 0.8)(Dm, H, Dh) * Dm ** (-0.5)), 'Wo': _w((lambda *s: torch.randn(*s, dtype=torch.bfloat16) * 0.8)(H, Dh, Dm) * (H * Dh) ** (-0.5)), 'seg_len': seg}
    _A_in = _A_setup()

    def _B_setup():
        B, S, D = (1, 2048, 448)
        return {'x': _w((lambda *s: torch.randn(*s, dtype=torch.bfloat16) * 0.05)(B, S, D)), 'wqkv': _w((lambda *s: torch.randn(*s, dtype=torch.bfloat16) * 1.6)(D, 3 * D)), 'wo': _w((lambda *s: torch.randn(*s, dtype=torch.bfloat16) * 0.1)(D, D))}
    _B_in = _B_setup()
    return {'A_x': _A_in['x'], 'A_mem0': _A_in['mem0'], 'A_Wq': _A_in['Wq'], 'A_Wk': _A_in['Wk'], 'A_Wv': _A_in['Wv'], 'A_Wo': _A_in['Wo'], 'A_seg_len': _A_in['seg_len'], 'B_x': _B_in['x'], 'B_wqkv': _B_in['wqkv'], 'B_wo': _B_in['wo']}

def reference(A_x, A_mem0, A_Wq, A_Wk, A_Wv, A_Wo, A_seg_len, B_x, B_wqkv, B_wo):

    def _A_ref(x, mem0, Wq, Wk, Wv, Wo, seg_len):
        B, S, Dm = x.shape
        H, Dh = (Wq.shape[1], Wq.shape[2])
        M = mem0.shape[1]
        scale = Dh ** (-0.5)
        n_seg = S // seg_len
        L = M + seg_len
        idx = torch.arange(L)
        mask = (idx[:, None] < M) | (idx[:, None] >= idx[None, :])
        mem = mem0
        outs = []
        for s in range(n_seg):
            xs = x[:, s * seg_len:(s + 1) * seg_len, :].clone()
            h = torch.concatenate([mem, xs], axis=1)
            q = torch.einsum('btd,dhe->bhte', h, Wq)
            k = torch.einsum('btd,dhe->bhte', h, Wk)
            v = torch.einsum('btd,dhe->bhte', h, Wv)
            scores = torch.einsum('bhqe,bhke->bhqk', q, k) * scale
            scores = torch.where(mask[None, None], scores, -1000000000.0)
            p = _softmax(scores, axis=-1)
            o = torch.einsum('bhqk,bhke->bhqe', p, v)
            o = torch.einsum('bhte,hed->btd', o, Wo)
            mem = o[:, :M, :].clone()
            outs.append(o[:, M:, :])
        return torch.concatenate(outs, axis=1)

    def _B_ref(x, wqkv, wo):
        B, S, D = x.shape
        H = 16
        Dh = D // H
        qkv = (lambda x, *d: x.permute(*d))((x @ wqkv).reshape(B, S, 3, H, Dh), 2, 0, 3, 1, 4)
        q, k, v = (qkv[0], qkv[1], qkv[2])
        phi = lambda t: torch.where(t > 0, t + 1, torch.exp(t)) + 1e-06
        pq, pk = (phi(q), phi(k))
        kv = torch.einsum('bhsd,bhse->bhde', pk, v)
        z = torch.einsum('bhsd->bhd', pk)
        num = torch.einsum('bhqd,bhde->bhqe', pq, kv)
        den = torch.einsum('bhqd,bhd->bhq', pq, z)[..., None] + 1e-06
        o = num / den
        return (lambda x, *d: x.permute(*d))(o, 0, 2, 1, 3).reshape(B, S, D) @ wo
    a = _A_ref(A_x, A_mem0, A_Wq, A_Wk, A_Wv, A_Wo, A_seg_len)
    b = _B_ref(B_x, B_wqkv, B_wo)
    return torch.concatenate([a, b], axis=-1)
```

```cpp
#include <cuda_runtime.h>
#include <cuda_bf16.h>
#include <cuda_fp16.h>
#include <cuda.h>
#include <stdint.h>

#define DEVI __device__ __forceinline__
#define WAIT_LIMIT (1 << 24)
#define POLL_DELAY 200

constexpr int SEQ = 2048, DM = 448, NH = 16, DH = 256, NMEM = 8, SEG = 32, NSEG = 64;
constexpr int NTILE = 28;
constexpr int NKS = 28;
constexpr int NCHUNK = 56;
constexpr int OUTW = 896;
constexpr int CS = 5;

__device__ __align__(128) uint4 g_WF[NH * 2 * NTILE * NKS * 32];
__device__ __align__(128) unsigned long long g_R[4 * NCHUNK * 32];
__device__ uint32_t g_beta[512];
__device__ uint32_t g_xmax[NSEG * 6];
__device__ __align__(128) uint4 g_TX[NSEG * NH * NTILE * 64];
__device__ __align__(128) uint4 g_VX[NSEG * NH * NTILE * 64];
__device__ __align__(128) uint4 g_VM[NSEG * NH * NTILE * 16];
__device__ __align__(128) uint32_t g_MEM[NSEG * NCHUNK * 32];
__device__ __align__(128) float g_KV[NH * 32 * 32];
constexpr int NFLAGS = 6 * NSEG;
__device__ unsigned int g_flags[NFLAGS];

DEVI uint32_t smem_u32(const void* p) { return (uint32_t)__cvta_generic_to_shared(p); }
DEVI void mbar_init(uint32_t a, uint32_t cnt) { asm volatile("mbarrier.init.shared::cta.b64 [%0], %1;" :: "r"(a), "r"(cnt) : "memory"); }
DEVI void mbar_expect_tx(uint32_t a, uint32_t bytes) { asm volatile("mbarrier.arrive.expect_tx.shared::cta.b64 _, [%0], %1;" :: "r"(a), "r"(bytes) : "memory"); }
DEVI void mbar_arrive(uint32_t a) { asm volatile("mbarrier.arrive.shared::cta.b64 _, [%0];" :: "r"(a) : "memory"); }
DEVI bool mbar_try(uint32_t a, uint32_t parity) {
    uint32_t ok;
    asm volatile("{\n.reg .pred p;\nmbarrier.try_wait.parity.shared::cta.b64 p, [%1], %2;\nselp.u32 %0, 1, 0, p;\n}" : "=r"(ok) : "r"(a), "r"(parity) : "memory");
    return ok != 0;
}
DEVI void mbar_wait(uint32_t a, uint32_t parity) {
    int spin = 0;
    while (!mbar_try(a, parity)) {
        if (++spin > WAIT_LIMIT) __trap();
    }
}
DEVI uint32_t mapa(uint32_t a, uint32_t rank) { uint32_t r; asm volatile("mapa.shared::cluster.u32 %0, %1, %2;" : "=r"(r) : "r"(a), "r"(rank)); return r; }
DEVI void st_async32(uint32_t addr, uint32_t v, uint32_t mbar) {
    asm volatile("st.async.weak.shared::cluster.mbarrier::complete_tx::bytes.b32 [%0], %1, [%2];" :: "r"(addr), "r"(v), "r"(mbar) : "memory");
}
DEVI void cluster_sync() { asm volatile("barrier.cluster.arrive.release.aligned;\nbarrier.cluster.wait.acquire.aligned;" ::: "memory"); }
DEVI void fence_proxy_async() { asm volatile("fence.proxy.async.shared::cta;" ::: "memory"); }
DEVI void fence_proxy_async_all() { asm volatile("fence.proxy.async;" ::: "memory"); }
DEVI void named_bar_sync(int id, int n) { asm volatile("bar.sync %0, %1;" :: "r"(id), "r"(n) : "memory"); }
DEVI void named_bar_arrive(int id, int n) { asm volatile("bar.arrive %0, %1;" :: "r"(id), "r"(n) : "memory"); }

DEVI void tma_load_2d(uint32_t dst, const CUtensorMap* tm, int c0, int c1, uint32_t mbar) {
    asm volatile("cp.async.bulk.tensor.2d.shared::cluster.global.mbarrier::complete_tx::bytes [%0], [%1, {%3, %4}], [%2];"
        :: "r"(dst), "l"((uint64_t)tm), "r"(mbar), "r"(c0), "r"(c1) : "memory");
}
DEVI void tma_load_2d_mc(uint32_t dst, const CUtensorMap* tm, int c0, int c1, uint32_t mbar, uint16_t mask) {
    asm volatile("cp.async.bulk.tensor.2d.shared::cluster.global.mbarrier::complete_tx::bytes.multicast::cluster [%0], [%1, {%3, %4}], [%2], %5;"
        :: "r"(dst), "l"((uint64_t)tm), "r"(mbar), "r"(c0), "r"(c1), "h"(mask) : "memory");
}
DEVI void bulk_load(uint32_t dst, const void* src, uint32_t bytes, uint32_t mbar) {
    asm volatile("cp.async.bulk.shared::cluster.global.mbarrier::complete_tx::bytes [%0], [%1], %2, [%3];"
        :: "r"(dst), "l"(src), "r"(bytes), "r"(mbar) : "memory");
}

DEVI void wg_fence() { asm volatile("wgmma.fence.sync.aligned;" ::: "memory"); }
DEVI void wg_commit() { asm volatile("wgmma.commit_group.sync.aligned;" ::: "memory"); }
template <int N> DEVI void wg_wait() { asm volatile("wgmma.wait_group.sync.aligned %0;" :: "n"(N) : "memory"); }
DEVI uint64_t mkdesc(uint32_t saddr, uint32_t lbo, uint32_t sbo, uint32_t swz) {
    return (uint64_t)((saddr & 0x3FFFF) >> 4) | ((uint64_t)((lbo >> 4) & 0x3FFF) << 16) | ((uint64_t)((sbo >> 4) & 0x3FFF) << 32) | ((uint64_t)swz << 62);
}
DEVI void ldsm_x4(uint32_t& r0, uint32_t& r1, uint32_t& r2, uint32_t& r3, uint32_t addr) {
    asm volatile("ldmatrix.sync.aligned.m8n8.x4.shared.b16 {%0,%1,%2,%3}, [%4];" : "=r"(r0), "=r"(r1), "=r"(r2), "=r"(r3) : "r"(addr) : "memory");
}
DEVI void ldsm_x4_t(uint32_t& r0, uint32_t& r1, uint32_t& r2, uint32_t& r3, uint32_t addr) {
    asm volatile("ldmatrix.sync.aligned.m8n8.x4.trans.shared.b16 {%0,%1,%2,%3}, [%4];" : "=r"(r0), "=r"(r1), "=r"(r2), "=r"(r3) : "r"(addr) : "memory");
}
DEVI void ldsm_x2(uint32_t& r0, uint32_t& r1, uint32_t addr) {
    asm volatile("ldmatrix.sync.aligned.m8n8.x2.shared.b16 {%0,%1}, [%2];" : "=r"(r0), "=r"(r1) : "r"(addr) : "memory");
}
DEVI void ldsm_x2_t(uint32_t& r0, uint32_t& r1, uint32_t addr) {
    asm volatile("ldmatrix.sync.aligned.m8n8.x2.trans.shared.b16 {%0,%1}, [%2];" : "=r"(r0), "=r"(r1) : "r"(addr) : "memory");
}
DEVI void stsm_x4(uint32_t addr, uint32_t r0, uint32_t r1, uint32_t r2, uint32_t r3) {
    asm volatile("stmatrix.sync.aligned.m8n8.x4.shared.b16 [%0], {%1,%2,%3,%4};" :: "r"(addr), "r"(r0), "r"(r1), "r"(r2), "r"(r3) : "memory");
}
DEVI void stsm_x4_t(uint32_t addr, uint32_t r0, uint32_t r1, uint32_t r2, uint32_t r3) {
    asm volatile("stmatrix.sync.aligned.m8n8.x4.trans.shared.b16 [%0], {%1,%2,%3,%4};" :: "r"(addr), "r"(r0), "r"(r1), "r"(r2), "r"(r3) : "memory");
}
DEVI uint32_t movm(uint32_t a) { uint32_t d; asm volatile("movmatrix.sync.aligned.m8n8.trans.b16 %0, %1;" : "=r"(d) : "r"(a)); return d; }
DEVI void hmma(float* d, uint32_t a0, uint32_t a1, uint32_t a2, uint32_t a3, uint32_t b0, uint32_t b1) {
    asm volatile("mma.sync.aligned.m16n8k16.row.col.f32.bf16.bf16.f32 {%0,%1,%2,%3}, {%4,%5,%6,%7}, {%8,%9}, {%0,%1,%2,%3};"
        : "+f"(d[0]), "+f"(d[1]), "+f"(d[2]), "+f"(d[3]) : "r"(a0), "r"(a1), "r"(a2), "r"(a3), "r"(b0), "r"(b1));
}
DEVI uint32_t pack_bf16(float lo, float hi) { uint32_t r; asm("cvt.rn.bf16x2.f32 %0, %1, %2;" : "=r"(r) : "f"(hi), "f"(lo)); return r; }
DEVI float ex2(float x) { float y; asm("ex2.approx.ftz.f32 %0, %1;" : "=f"(y) : "f"(x)); return y; }
DEVI float rcp_approx(float x) { float y; asm("rcp.approx.ftz.f32 %0, %1;" : "=f"(y) : "f"(x)); return y; }
DEVI float2 lds64(uint32_t a) { float2 v; asm volatile("ld.shared.v2.f32 {%0,%1}, [%2];" : "=f"(v.x), "=f"(v.y) : "r"(a) : "memory"); return v; }
DEVI void sts64(uint32_t a, float x, float y) { asm volatile("st.shared.v2.f32 [%0], {%1,%2};" :: "r"(a), "f"(x), "f"(y) : "memory"); }
DEVI void sts32(uint32_t a, uint32_t x) { asm volatile("st.shared.b32 [%0], %1;" :: "r"(a), "r"(x) : "memory"); }
DEVI void red_release_add(unsigned int* p, unsigned int v) { asm volatile("red.release.gpu.global.add.u32 [%0], %1;" :: "l"(p), "r"(v) : "memory"); }
DEVI unsigned int ld_acquire(const unsigned int* p) { unsigned int v; asm volatile("ld.acquire.gpu.global.u32 %0, [%1];" : "=r"(v) : "l"(p) : "memory"); return v; }
DEVI void pdl_wait() { asm volatile("griddepcontrol.wait;" ::: "memory"); }
DEVI void pdl_launch() { asm volatile("griddepcontrol.launch_dependents;" ::: "memory"); }

#define TL_MIN(i) do {} while (0)
#define TL_MAX(i) do {} while (0)
__device__ __forceinline__ void wg_ss224_kk(float* d, uint64_t da, uint64_t db, int acc) {
    asm volatile("{\n.reg .pred p;\nsetp.ne.b32 p, %114, 0;\n"
        "wgmma.mma_async.sync.aligned.m64n224k16.f32.bf16.bf16 {%0,%1,%2,%3,%4,%5,%6,%7,%8,%9,%10,%11,%12,%13,%14,%15,%16,%17,%18,%19,%20,%21,%22,%23,%24,%25,%26,%27,%28,%29,%30,%31,%32,%33,%34,%35,%36,%37,%38,%39,%40,%41,%42,%43,%44,%45,%46,%47,%48,%49,%50,%51,%52,%53,%54,%55,%56,%57,%58,%59,%60,%61,%62,%63,%64,%65,%66,%67,%68,%69,%70,%71,%72,%73,%74,%75,%76,%77,%78,%79,%80,%81,%82,%83,%84,%85,%86,%87,%88,%89,%90,%91,%92,%93,%94,%95,%96,%97,%98,%99,%100,%101,%102,%103,%104,%105,%106,%107,%108,%109,%110,%111}, %112, %113, p, 1, 1, 0, 0;\n}\n"
        : "+f"(d[0]), "+f"(d[1]), "+f"(d[2]), "+f"(d[3]), "+f"(d[4]), "+f"(d[5]), "+f"(d[6]), "+f"(d[7]), "+f"(d[8]), "+f"(d[9]), "+f"(d[10]), "+f"(d[11]), "+f"(d[12]), "+f"(d[13]), "+f"(d[14]), "+f"(d[15]), "+f"(d[16]), "+f"(d[17]), "+f"(d[18]), "+f"(d[19]), "+f"(d[20]), "+f"(d[21]), "+f"(d[22]), "+f"(d[23]), "+f"(d[24]), "+f"(d[25]), "+f"(d[26]), "+f"(d[27]), "+f"(d[28]), "+f"(d[29]), "+f"(d[30]), "+f"(d[31]), "+f"(d[32]), "+f"(d[33]), "+f"(d[34]), "+f"(d[35]), "+f"(d[36]), "+f"(d[37]), "+f"(d[38]), "+f"(d[39]), "+f"(d[40]), "+f"(d[41]), "+f"(d[42]), "+f"(d[43]), "+f"(d[44]), "+f"(d[45]), "+f"(d[46]), "+f"(d[47]), "+f"(d[48]), "+f"(d[49]), "+f"(d[50]), "+f"(d[51]), "+f"(d[52]), "+f"(d[53]), "+f"(d[54]), "+f"(d[55]), "+f"(d[56]), "+f"(d[57]), "+f"(d[58]), "+f"(d[59]), "+f"(d[60]), "+f"(d[61]), "+f"(d[62]), "+f"(d[63]), "+f"(d[64]), "+f"(d[65]), "+f"(d[66]), "+f"(d[67]), "+f"(d[68]), "+f"(d[69]), "+f"(d[70]), "+f"(d[71]), "+f"(d[72]), "+f"(d[73]), "+f"(d[74]), "+f"(d[75]), "+f"(d[76]), "+f"(d[77]), "+f"(d[78]), "+f"(d[79]), "+f"(d[80]), "+f"(d[81]), "+f"(d[82]), "+f"(d[83]), "+f"(d[84]), "+f"(d[85]), "+f"(d[86]), "+f"(d[87]), "+f"(d[88]), "+f"(d[89]), "+f"(d[90]), "+f"(d[91]), "+f"(d[92]), "+f"(d[93]), "+f"(d[94]), "+f"(d[95]), "+f"(d[96]), "+f"(d[97]), "+f"(d[98]), "+f"(d[99]), "+f"(d[100]), "+f"(d[101]), "+f"(d[102]), "+f"(d[103]), "+f"(d[104]), "+f"(d[105]), "+f"(d[106]), "+f"(d[107]), "+f"(d[108]), "+f"(d[109]), "+f"(d[110]), "+f"(d[111])
        : "l"(da), "l"(db), "r"(acc));
}
__device__ __forceinline__ void wg_ss224_mk(float* d, uint64_t da, uint64_t db, int acc) {
    asm volatile("{\n.reg .pred p;\nsetp.ne.b32 p, %114, 0;\n"
        "wgmma.mma_async.sync.aligned.m64n224k16.f32.bf16.bf16 {%0,%1,%2,%3,%4,%5,%6,%7,%8,%9,%10,%11,%12,%13,%14,%15,%16,%17,%18,%19,%20,%21,%22,%23,%24,%25,%26,%27,%28,%29,%30,%31,%32,%33,%34,%35,%36,%37,%38,%39,%40,%41,%42,%43,%44,%45,%46,%47,%48,%49,%50,%51,%52,%53,%54,%55,%56,%57,%58,%59,%60,%61,%62,%63,%64,%65,%66,%67,%68,%69,%70,%71,%72,%73,%74,%75,%76,%77,%78,%79,%80,%81,%82,%83,%84,%85,%86,%87,%88,%89,%90,%91,%92,%93,%94,%95,%96,%97,%98,%99,%100,%101,%102,%103,%104,%105,%106,%107,%108,%109,%110,%111}, %112, %113, p, 1, 1, 1, 0;\n}\n"
        : "+f"(d[0]), "+f"(d[1]), "+f"(d[2]), "+f"(d[3]), "+f"(d[4]), "+f"(d[5]), "+f"(d[6]), "+f"(d[7]), "+f"(d[8]), "+f"(d[9]), "+f"(d[10]), "+f"(d[11]), "+f"(d[12]), "+f"(d[13]), "+f"(d[14]), "+f"(d[15]), "+f"(d[16]), "+f"(d[17]), "+f"(d[18]), "+f"(d[19]), "+f"(d[20]), "+f"(d[21]), "+f"(d[22]), "+f"(d[23]), "+f"(d[24]), "+f"(d[25]), "+f"(d[26]), "+f"(d[27]), "+f"(d[28]), "+f"(d[29]), "+f"(d[30]), "+f"(d[31]), "+f"(d[32]), "+f"(d[33]), "+f"(d[34]), "+f"(d[35]), "+f"(d[36]), "+f"(d[37]), "+f"(d[38]), "+f"(d[39]), "+f"(d[40]), "+f"(d[41]), "+f"(d[42]), "+f"(d[43]), "+f"(d[44]), "+f"(d[45]), "+f"(d[46]), "+f"(d[47]), "+f"(d[48]), "+f"(d[49]), "+f"(d[50]), "+f"(d[51]), "+f"(d[52]), "+f"(d[53]), "+f"(d[54]), "+f"(d[55]), "+f"(d[56]), "+f"(d[57]), "+f"(d[58]), "+f"(d[59]), "+f"(d[60]), "+f"(d[61]), "+f"(d[62]), "+f"(d[63]), "+f"(d[64]), "+f"(d[65]), "+f"(d[66]), "+f"(d[67]), "+f"(d[68]), "+f"(d[69]), "+f"(d[70]), "+f"(d[71]), "+f"(d[72]), "+f"(d[73]), "+f"(d[74]), "+f"(d[75]), "+f"(d[76]), "+f"(d[77]), "+f"(d[78]), "+f"(d[79]), "+f"(d[80]), "+f"(d[81]), "+f"(d[82]), "+f"(d[83]), "+f"(d[84]), "+f"(d[85]), "+f"(d[86]), "+f"(d[87]), "+f"(d[88]), "+f"(d[89]), "+f"(d[90]), "+f"(d[91]), "+f"(d[92]), "+f"(d[93]), "+f"(d[94]), "+f"(d[95]), "+f"(d[96]), "+f"(d[97]), "+f"(d[98]), "+f"(d[99]), "+f"(d[100]), "+f"(d[101]), "+f"(d[102]), "+f"(d[103]), "+f"(d[104]), "+f"(d[105]), "+f"(d[106]), "+f"(d[107]), "+f"(d[108]), "+f"(d[109]), "+f"(d[110]), "+f"(d[111])
        : "l"(da), "l"(db), "r"(acc));
}
__device__ __forceinline__ void wg_rs32(float* d, uint32_t a0, uint32_t a1, uint32_t a2, uint32_t a3, uint64_t db, int acc) {
    asm volatile("{\n.reg .pred p;\nsetp.ne.b32 p, %21, 0;\n"
        "wgmma.mma_async.sync.aligned.m64n32k16.f32.bf16.bf16 {%0,%1,%2,%3,%4,%5,%6,%7,%8,%9,%10,%11,%12,%13,%14,%15}, {%16,%17,%18,%19}, %20, p, 1, 1, 0;\n}\n"
        : "+f"(d[0]), "+f"(d[1]), "+f"(d[2]), "+f"(d[3]), "+f"(d[4]), "+f"(d[5]), "+f"(d[6]), "+f"(d[7]), "+f"(d[8]), "+f"(d[9]), "+f"(d[10]), "+f"(d[11]), "+f"(d[12]), "+f"(d[13]), "+f"(d[14]), "+f"(d[15])
        : "r"(a0), "r"(a1), "r"(a2), "r"(a3), "l"(db), "r"(acc));
}
__device__ __forceinline__ void wg_rs64(float* d, uint32_t a0, uint32_t a1, uint32_t a2, uint32_t a3, uint64_t db, int acc) {
    asm volatile("{\n.reg .pred p;\nsetp.ne.b32 p, %37, 0;\n"
        "wgmma.mma_async.sync.aligned.m64n64k16.f32.bf16.bf16 {%0,%1,%2,%3,%4,%5,%6,%7,%8,%9,%10,%11,%12,%13,%14,%15,%16,%17,%18,%19,%20,%21,%22,%23,%24,%25,%26,%27,%28,%29,%30,%31}, {%32,%33,%34,%35}, %36, p, 1, 1, 0;\n}\n"
        : "+f"(d[0]), "+f"(d[1]), "+f"(d[2]), "+f"(d[3]), "+f"(d[4]), "+f"(d[5]), "+f"(d[6]), "+f"(d[7]), "+f"(d[8]), "+f"(d[9]), "+f"(d[10]), "+f"(d[11]), "+f"(d[12]), "+f"(d[13]), "+f"(d[14]), "+f"(d[15]), "+f"(d[16]), "+f"(d[17]), "+f"(d[18]), "+f"(d[19]), "+f"(d[20]), "+f"(d[21]), "+f"(d[22]), "+f"(d[23]), "+f"(d[24]), "+f"(d[25]), "+f"(d[26]), "+f"(d[27]), "+f"(d[28]), "+f"(d[29]), "+f"(d[30]), "+f"(d[31])
        : "r"(a0), "r"(a1), "r"(a2), "r"(a3), "l"(db), "r"(acc));
}
__device__ __forceinline__ void wg_ss40_mk(float* d, uint64_t da, uint64_t db, int acc) {
    asm volatile("{\n.reg .pred p;\nsetp.ne.b32 p, %22, 0;\n"
        "wgmma.mma_async.sync.aligned.m64n40k16.f32.bf16.bf16 {%0,%1,%2,%3,%4,%5,%6,%7,%8,%9,%10,%11,%12,%13,%14,%15,%16,%17,%18,%19}, %20, %21, p, 1, 1, 1, 0;\n}\n"
        : "+f"(d[0]), "+f"(d[1]), "+f"(d[2]), "+f"(d[3]), "+f"(d[4]), "+f"(d[5]), "+f"(d[6]), "+f"(d[7]), "+f"(d[8]), "+f"(d[9]), "+f"(d[10]), "+f"(d[11]), "+f"(d[12]), "+f"(d[13]), "+f"(d[14]), "+f"(d[15]), "+f"(d[16]), "+f"(d[17]), "+f"(d[18]), "+f"(d[19])
        : "l"(da), "l"(db), "r"(acc));
}
__device__ __forceinline__ void wg_ss32_kk(float* d, uint64_t da, uint64_t db, int acc) {
    asm volatile("{\n.reg .pred p;\nsetp.ne.b32 p, %18, 0;\n"
        "wgmma.mma_async.sync.aligned.m64n32k16.f32.bf16.bf16 {%0,%1,%2,%3,%4,%5,%6,%7,%8,%9,%10,%11,%12,%13,%14,%15}, %16, %17, p, 1, 1, 0, 0;\n}\n"
        : "+f"(d[0]), "+f"(d[1]), "+f"(d[2]), "+f"(d[3]), "+f"(d[4]), "+f"(d[5]), "+f"(d[6]), "+f"(d[7]), "+f"(d[8]), "+f"(d[9]), "+f"(d[10]), "+f"(d[11]), "+f"(d[12]), "+f"(d[13]), "+f"(d[14]), "+f"(d[15])
        : "l"(da), "l"(db), "r"(acc));
}
__device__ __forceinline__ void wg_ss192_kn(float* d, uint64_t da, uint64_t db, int acc) {
    asm volatile("{\n.reg .pred p;\nsetp.ne.b32 p, %98, 0;\n"
        "wgmma.mma_async.sync.aligned.m64n192k16.f32.bf16.bf16 {%0,%1,%2,%3,%4,%5,%6,%7,%8,%9,%10,%11,%12,%13,%14,%15,%16,%17,%18,%19,%20,%21,%22,%23,%24,%25,%26,%27,%28,%29,%30,%31,%32,%33,%34,%35,%36,%37,%38,%39,%40,%41,%42,%43,%44,%45,%46,%47,%48,%49,%50,%51,%52,%53,%54,%55,%56,%57,%58,%59,%60,%61,%62,%63,%64,%65,%66,%67,%68,%69,%70,%71,%72,%73,%74,%75,%76,%77,%78,%79,%80,%81,%82,%83,%84,%85,%86,%87,%88,%89,%90,%91,%92,%93,%94,%95}, %96, %97, p, 1, 1, 0, 1;\n}\n"
        : "+f"(d[0]), "+f"(d[1]), "+f"(d[2]), "+f"(d[3]), "+f"(d[4]), "+f"(d[5]), "+f"(d[6]), "+f"(d[7]), "+f"(d[8]), "+f"(d[9]), "+f"(d[10]), "+f"(d[11]), "+f"(d[12]), "+f"(d[13]), "+f"(d[14]), "+f"(d[15]), "+f"(d[16]), "+f"(d[17]), "+f"(d[18]), "+f"(d[19]), "+f"(d[20]), "+f"(d[21]), "+f"(d[22]), "+f"(d[23]), "+f"(d[24]), "+f"(d[25]), "+f"(d[26]), "+f"(d[27]), "+f"(d[28]), "+f"(d[29]), "+f"(d[30]), "+f"(d[31]), "+f"(d[32]), "+f"(d[33]), "+f"(d[34]), "+f"(d[35]), "+f"(d[36]), "+f"(d[37]), "+f"(d[38]), "+f"(d[39]), "+f"(d[40]), "+f"(d[41]), "+f"(d[42]), "+f"(d[43]), "+f"(d[44]), "+f"(d[45]), "+f"(d[46]), "+f"(d[47]), "+f"(d[48]), "+f"(d[49]), "+f"(d[50]), "+f"(d[51]), "+f"(d[52]), "+f"(d[53]), "+f"(d[54]), "+f"(d[55]), "+f"(d[56]), "+f"(d[57]), "+f"(d[58]), "+f"(d[59]), "+f"(d[60]), "+f"(d[61]), "+f"(d[62]), "+f"(d[63]), "+f"(d[64]), "+f"(d[65]), "+f"(d[66]), "+f"(d[67]), "+f"(d[68]), "+f"(d[69]), "+f"(d[70]), "+f"(d[71]), "+f"(d[72]), "+f"(d[73]), "+f"(d[74]), "+f"(d[75]), "+f"(d[76]), "+f"(d[77]), "+f"(d[78]), "+f"(d[79]), "+f"(d[80]), "+f"(d[81]), "+f"(d[82]), "+f"(d[83]), "+f"(d[84]), "+f"(d[85]), "+f"(d[86]), "+f"(d[87]), "+f"(d[88]), "+f"(d[89]), "+f"(d[90]), "+f"(d[91]), "+f"(d[92]), "+f"(d[93]), "+f"(d[94]), "+f"(d[95])
        : "l"(da), "l"(db), "r"(acc));
}
__device__ __forceinline__ void wg_ss256_kn(float* d, uint64_t da, uint64_t db, int acc) {
    asm volatile("{\n.reg .pred p;\nsetp.ne.b32 p, %130, 0;\n"
        "wgmma.mma_async.sync.aligned.m64n256k16.f32.bf16.bf16 {%0,%1,%2,%3,%4,%5,%6,%7,%8,%9,%10,%11,%12,%13,%14,%15,%16,%17,%18,%19,%20,%21,%22,%23,%24,%25,%26,%27,%28,%29,%30,%31,%32,%33,%34,%35,%36,%37,%38,%39,%40,%41,%42,%43,%44,%45,%46,%47,%48,%49,%50,%51,%52,%53,%54,%55,%56,%57,%58,%59,%60,%61,%62,%63,%64,%65,%66,%67,%68,%69,%70,%71,%72,%73,%74,%75,%76,%77,%78,%79,%80,%81,%82,%83,%84,%85,%86,%87,%88,%89,%90,%91,%92,%93,%94,%95,%96,%97,%98,%99,%100,%101,%102,%103,%104,%105,%106,%107,%108,%109,%110,%111,%112,%113,%114,%115,%116,%117,%118,%119,%120,%121,%122,%123,%124,%125,%126,%127}, %128, %129, p, 1, 1, 0, 1;\n}\n"
        : "+f"(d[0]), "+f"(d[1]), "+f"(d[2]), "+f"(d[3]), "+f"(d[4]), "+f"(d[5]), "+f"(d[6]), "+f"(d[7]), "+f"(d[8]), "+f"(d[9]), "+f"(d[10]), "+f"(d[11]), "+f"(d[12]), "+f"(d[13]), "+f"(d[14]), "+f"(d[15]), "+f"(d[16]), "+f"(d[17]), "+f"(d[18]), "+f"(d[19]), "+f"(d[20]), "+f"(d[21]), "+f"(d[22]), "+f"(d[23]), "+f"(d[24]), "+f"(d[25]), "+f"(d[26]), "+f"(d[27]), "+f"(d[28]), "+f"(d[29]), "+f"(d[30]), "+f"(d[31]), "+f"(d[32]), "+f"(d[33]), "+f"(d[34]), "+f"(d[35]), "+f"(d[36]), "+f"(d[37]), "+f"(d[38]), "+f"(d[39]), "+f"(d[40]), "+f"(d[41]), "+f"(d[42]), "+f"(d[43]), "+f"(d[44]), "+f"(d[45]), "+f"(d[46]), "+f"(d[47]), "+f"(d[48]), "+f"(d[49]), "+f"(d[50]), "+f"(d[51]), "+f"(d[52]), "+f"(d[53]), "+f"(d[54]), "+f"(d[55]), "+f"(d[56]), "+f"(d[57]), "+f"(d[58]), "+f"(d[59]), "+f"(d[60]), "+f"(d[61]), "+f"(d[62]), "+f"(d[63]), "+f"(d[64]), "+f"(d[65]), "+f"(d[66]), "+f"(d[67]), "+f"(d[68]), "+f"(d[69]), "+f"(d[70]), "+f"(d[71]), "+f"(d[72]), "+f"(d[73]), "+f"(d[74]), "+f"(d[75]), "+f"(d[76]), "+f"(d[77]), "+f"(d[78]), "+f"(d[79]), "+f"(d[80]), "+f"(d[81]), "+f"(d[82]), "+f"(d[83]), "+f"(d[84]), "+f"(d[85]), "+f"(d[86]), "+f"(d[87]), "+f"(d[88]), "+f"(d[89]), "+f"(d[90]), "+f"(d[91]), "+f"(d[92]), "+f"(d[93]), "+f"(d[94]), "+f"(d[95]), "+f"(d[96]), "+f"(d[97]), "+f"(d[98]), "+f"(d[99]), "+f"(d[100]), "+f"(d[101]), "+f"(d[102]), "+f"(d[103]), "+f"(d[104]), "+f"(d[105]), "+f"(d[106]), "+f"(d[107]), "+f"(d[108]), "+f"(d[109]), "+f"(d[110]), "+f"(d[111]), "+f"(d[112]), "+f"(d[113]), "+f"(d[114]), "+f"(d[115]), "+f"(d[116]), "+f"(d[117]), "+f"(d[118]), "+f"(d[119]), "+f"(d[120]), "+f"(d[121]), "+f"(d[122]), "+f"(d[123]), "+f"(d[124]), "+f"(d[125]), "+f"(d[126]), "+f"(d[127])
        : "l"(da), "l"(db), "r"(acc));
}
__device__ __forceinline__ void wg_ss64_mn(float* d, uint64_t da, uint64_t db, int acc) {
    asm volatile("{\n.reg .pred p;\nsetp.ne.b32 p, %34, 0;\n"
        "wgmma.mma_async.sync.aligned.m64n64k16.f32.bf16.bf16 {%0,%1,%2,%3,%4,%5,%6,%7,%8,%9,%10,%11,%12,%13,%14,%15,%16,%17,%18,%19,%20,%21,%22,%23,%24,%25,%26,%27,%28,%29,%30,%31}, %32, %33, p, 1, 1, 1, 1;\n}\n"
        : "+f"(d[0]), "+f"(d[1]), "+f"(d[2]), "+f"(d[3]), "+f"(d[4]), "+f"(d[5]), "+f"(d[6]), "+f"(d[7]), "+f"(d[8]), "+f"(d[9]), "+f"(d[10]), "+f"(d[11]), "+f"(d[12]), "+f"(d[13]), "+f"(d[14]), "+f"(d[15]), "+f"(d[16]), "+f"(d[17]), "+f"(d[18]), "+f"(d[19]), "+f"(d[20]), "+f"(d[21]), "+f"(d[22]), "+f"(d[23]), "+f"(d[24]), "+f"(d[25]), "+f"(d[26]), "+f"(d[27]), "+f"(d[28]), "+f"(d[29]), "+f"(d[30]), "+f"(d[31])
        : "l"(da), "l"(db), "r"(acc));
}

constexpr int PREP_NSTG = 5;
constexpr int PREP_BSTG = 224 * 128;
constexpr int PREP_SMEM = 65536 + PREP_NSTG * PREP_BSTG + 1024 + 256;

__global__ void __launch_bounds__(384, 1)
k_prep(const __grid_constant__ CUtensorMap tmWq, const __grid_constant__ CUtensorMap tmWk,
       const __grid_constant__ CUtensorMap tmWv, const __grid_constant__ CUtensorMap tmWo, const __nv_bfloat16* __restrict__ x) {
    extern __shared__ uint8_t smem_raw[];
    const uint32_t sbase = (smem_u32(smem_raw) + 1023) & ~1023u;
    const uint32_t sA = sbase, sB = sbase + 65536, sBar = sB + PREP_NSTG * PREP_BSTG;
    const uint32_t barA = sBar, barFull = sBar + 8, barEmpty = sBar + 8 + 8 * PREP_NSTG;
    const int h = blockIdx.x >> 3, type = (blockIdx.x >> 2) & 1, mp = blockIdx.x & 3;
    const int warp = __shfl_sync(0xffffffff, threadIdx.x >> 5, 0), lane = threadIdx.x & 31;
    const int c0 = mp * 128;
    pdl_launch();
    if (threadIdx.x == 0) TL_MIN(0);
    if (threadIdx.x == 0) {
        mbar_init(barA, 1);
        for (int i = 0; i < PREP_NSTG; i++) { mbar_init(barFull + 8 * i, 1); mbar_init(barEmpty + 8 * i, 2); }
        asm volatile("fence.mbarrier_init.release.cluster;" ::: "memory");
    }
    __syncthreads();
    if (warp >= 8) {
        if (warp == 8) {
            __syncwarp();
            if (lane == 0) {
                mbar_expect_tx(barA, 65536);
                if (type == 0) { for (int kc = 0; kc < 4; kc++) tma_load_2d(sA + kc * 16384, &tmWk, h * DH + kc * 64, c0, barA); }
                else { for (int i = 0; i < 2; i++) tma_load_2d(sA + i * 32768, &tmWo, c0 + i * 64, h * DH, barA); }
                const CUtensorMap* tb = type == 0 ? &tmWq : &tmWv;
                for (int it = 0; it < 8; it++) {
                    const int st = it % PREP_NSTG;
                    if (it >= PREP_NSTG) mbar_wait(barEmpty + 8 * st, ((it / PREP_NSTG) - 1) & 1);
                    mbar_expect_tx(barFull + 8 * st, PREP_BSTG);
                    tma_load_2d(sB + st * PREP_BSTG, tb, h * DH + (it & 3) * 64, (it >> 2) * 224, barFull + 8 * st);
                }
            }
        } else {
            const int t = (warp - 9) * 32 + lane;
            const int nR = 4 * NCHUNK * 16;
            for (int i = blockIdx.x * 96 + t; i < nR; i += gridDim.x * 96) ((ulonglong2*)g_R)[i] = make_ulonglong2(0ull, 0ull);
            {
                const uint4* xs = (const uint4*)(x + (size_t)blockIdx.x * 16 * DM);
                uint32_t m = 0;
                for (int i = t; i < 16 * DM / 8; i += 96) {
                    const uint4 v = __ldg(xs + i);
                    m = __vmaxu2(m, __vmaxu2(__vmaxu2(v.x & 0x7FFF7FFFu, v.y & 0x7FFF7FFFu), __vmaxu2(v.z & 0x7FFF7FFFu, v.w & 0x7FFF7FFFu)));
                }
                m = __reduce_max_sync(0xffffffff, max(m & 0xFFFFu, m >> 16) << 16);
                if (lane == 0) g_xmax[(blockIdx.x >> 1) * 6 + (blockIdx.x & 1) * 3 + (warp - 9)] = m;
            }
            if (blockIdx.x == 0) for (int i = t; i < NFLAGS; i += 96) g_flags[i] = 0;
            if (blockIdx.x == 1) for (int i = t; i < NH * 32 * 32; i += 96) g_KV[i] = 0.f;
        }
    } else {
        const int wg = warp >> 2, w = warp & 3;
        float acc[112];
        mbar_wait(barA, 0);
        const float sc = type == 0 ? 0.0625f * 1.4426950408889634f : 1.0f;
        float rs0 = 0.f, rs1 = 0.f;
        for (int p = 0; p < 2; p++) {
            for (int kc = 0; kc < 4; kc++) {
                const int it = p * 4 + kc, st = it % PREP_NSTG;
                mbar_wait(barFull + 8 * st, (it / PREP_NSTG) & 1);
                wg_fence();
                #pragma unroll
                for (int ks = 0; ks < 4; ks++) {
                    const uint64_t db = mkdesc(sB + st * PREP_BSTG + ks * 32, 16, 1024, 1);
                    if (type == 0) wg_ss224_kk(acc, mkdesc(sA + kc * 16384 + wg * 8192 + ks * 32, 16, 1024, 1), db, (kc | ks) != 0);
                    else           wg_ss224_mk(acc, mkdesc(sA + wg * 32768 + (kc * 64 + ks * 16) * 128, 1024, 1024, 1), db, (kc | ks) != 0);
                }
                wg_commit();
                wg_wait<1>();
                if (kc > 0 && threadIdx.x % 128 == 0) mbar_arrive(barEmpty + 8 * ((it - 1) % PREP_NSTG));
            }
            wg_wait<0>();
            if (threadIdx.x % 128 == 0) mbar_arrive(barEmpty + 8 * ((p * 4 + 3) % PREP_NSTG));
            const int tile = (c0 >> 4) + wg * 4 + w;
            if (tile < NTILE) {
                uint4* dst = g_WF + ((size_t)((h * 2 + type) * NTILE + tile) * NKS + p * 14) * 32 + lane;
                #pragma unroll
                for (int j = 0; j < 14; j++) {
                    uint4 v;
                    v.x = pack_bf16(acc[8 * j + 0] * sc, acc[8 * j + 1] * sc);
                    v.y = pack_bf16(acc[8 * j + 2] * sc, acc[8 * j + 3] * sc);
                    v.z = pack_bf16(acc[8 * j + 4] * sc, acc[8 * j + 5] * sc);
                    v.w = pack_bf16(acc[8 * j + 6] * sc, acc[8 * j + 7] * sc);
                    dst[j * 32] = v;
                }
            }
            #pragma unroll
            for (int j = 0; j < 28; j++) { rs0 += fabsf(acc[4 * j]) + fabsf(acc[4 * j + 1]); rs1 += fabsf(acc[4 * j + 2]) + fabsf(acc[4 * j + 3]); }
        }
        if (type == 1) {
            rs0 += __shfl_xor_sync(0xffffffff, rs0, 1); rs0 += __shfl_xor_sync(0xffffffff, rs0, 2);
            rs1 += __shfl_xor_sync(0xffffffff, rs1, 1); rs1 += __shfl_xor_sync(0xffffffff, rs1, 2);
            const uint32_t m = __reduce_max_sync(0xffffffff, __float_as_uint(fmaxf(rs0, rs1)));
            if (lane == 0) g_beta[(h * 4 + mp) * 8 + warp] = m;
        }
        if (threadIdx.x == 0) TL_MAX(1);
    }
}

constexpr int CH_X = 0;
constexpr int CH_STGX = 3 * 28672;
constexpr int CH_MEM = CH_STGX + 2 * 8192;
constexpr int CH_SB = CH_MEM + 2 * 7168;
constexpr int CH_PL = CH_SB + 2 * 6400;
constexpr int CH_SS = CH_PL + 7680;
constexpr int CH_MAXW = CH_SS + 1280;
constexpr int CH_EXP = CH_MAXW + 128;
constexpr int CH_XM = CH_EXP + 64;
constexpr int CH_BAR = CH_XM + 256;
constexpr int CH_PROF = CH_BAR + 256;
constexpr int CH_SMEM = CH_PROF + 1024;
constexpr int B_X = 0, B_S = 3, B_STGX = 5, B_MAX = 7, B_STGM = 9, B_RED = 11, B_MEM = 12, B_STGF = 22;

#define PROF(slot) do {} while (0)
#define PROFG(slot) do {} while (0)

#define OPAQUE_LOCALS int lane = lane_; uint32_t sb = sb_; asm volatile("" : "+r"(lane), "+r"(sb)); const uint32_t bar = sb + CH_BAR;

#define MEM_GEMM_BODY(mb, mbar0) \
    _Pragma("unroll") for (int p = 0; p < 14; p++) { \
        const int q = (p + 3 * G) % 14;                \
        const int r = ((q / 3) - G + 5) % 5;           \
        if (q % 3 == 0) { \
            if (r == 0) { mbar_wait((mbar0) + 8 * G, ph); if (warp == 0) PROF(17); } \
            if (r == 1) { mbar_wait((mbar0) + 8 * ((G + 1) % 5), ph); mbar_wait((mbar0) + 8 * ((G + 2) % 5), ph); if (warp == 0) PROF(18); } \
            if (r == 3) { mbar_wait((mbar0) + 8 * ((G + 3) % 5), ph); mbar_wait((mbar0) + 8 * ((G + 4) % 5), ph); if (warp == 0) PROF(20); } \
        } \
        uint32_t b0, b1, b2, b3; \
        ldsm_x4_t(b0, b1, b2, b3, (mb) + q * 512); \
        hmma(d[(2 * p) & 3], wf[8 * q], wf[8 * q + 1], wf[8 * q + 2], wf[8 * q + 3], b0, b1); \
        hmma(d[(2 * p + 1) & 3], wf[8 * q + 4], wf[8 * q + 5], wf[8 * q + 6], wf[8 * q + 7], b2, b3); \
    }

#define SCORES() \
    { \
        const int c0 = tile * 16; \
        const uint32_t xa = sb + CH_X + (s % 3) * 28672 + (c0 >> 6) * 4096; \
        const int kap = ((c0 & 63) >> 3) + ((lane >> 3) & 1); \
        uint32_t hb[10]; \
        _Pragma("unroll") for (int v2 = 0; v2 < 2; v2++) { \
            const int j = 16 * v2 + 8 * (lane >> 4) + (lane & 7); \
            ldsm_x4(hb[4 * v2], hb[4 * v2 + 1], hb[4 * v2 + 2], hb[4 * v2 + 3], xa + j * 128 + ((kap ^ (lane & 7)) << 4)); \
        } \
        ldsm_x2_t(hb[8], hb[9], memt + ((c0 >> 3) + ((lane >> 3) & 1)) * 128 + (lane & 7) * 16); \
        _Pragma("unroll") for (int i = 0; i < 4; i++) d[0][i] = (d[0][i] + d[1][i]) + (d[2][i] + d[3][i]); \
        if (warp == 0) PROF(1); \
        const uint32_t a0 = movm(pack_bf16(d[0][0], d[0][1])), a2 = movm(pack_bf16(d[0][2], d[0][3])); \
        float sc[5][4]; \
        _Pragma("unroll") for (int nu = 0; nu < 5; nu++) { sc[nu][0] = sc[nu][1] = sc[nu][2] = sc[nu][3] = 0.f; hmma(sc[nu], a0, 0u, a2, 0u, hb[2 * nu], hb[2 * nu + 1]); } \
        const uint32_t pl = sb + CH_PL + lane * 8; \
        _Pragma("unroll") for (int nu = 0; nu < 5; nu++) sts64(pl + (warp * 5 + nu) * 256, sc[nu][0], sc[nu][1]); \
        named_bar_sync(1, 192); \
        if (warp == 0) PROF(2); \
        if (warp < 5) { \
            float2 v[6]; \
            _Pragma("unroll") for (int w = 0; w < 6; w++) v[w] = lds64(pl + (w * 5 + warp) * 256); \
            const float x = ((v[0].x + v[1].x) + (v[2].x + v[3].x)) + (v[4].x + v[5].x); \
            const float y = ((v[0].y + v[1].y) + (v[2].y + v[3].y)) + (v[4].y + v[5].y); \
              \
            const uint32_t off = CH_SB + pb * 3200 + (g * 5 + warp) * 128 + lane * 4, boff = CH_BAR + 8 * (B_S + pb); \
            uint32_t hv; asm("cvt.rn.satfinite.f16x2.f32 %0, %1, %2;" : "=r"(hv) : "f"(y * 0.015625f), "f"(x * 0.015625f)); \
            _Pragma("unroll") for (int c = 1; c < CS; c++) { const uint32_t rb = mapa(sb, (g + c) % CS); st_async32(rb + off, hv, rb + boff); } \
            sts32(sb + off, hv); \
            __syncwarp(); \
            if (lane == 0) mbar_arrive(sb + boff); \
        } \
        if (warp == 0) PROF(3); \
    }

#define LOAD_WEIGHTS() \
    uint32_t wf[112]; \
    { \
        const uint4* src = g_WF + ((size_t)((h * 2 + (isA ? 0 : 1)) * NTILE + tile) * NKS) * 32 + lane; \
        _Pragma("unroll") for (int k = 0; k < NKS; k++) { \
            uint4 v = __ldcg(src + k * 32); \
            if (!valid) v = make_uint4(0, 0, 0, 0); \
            wf[4 * k] = v.x; wf[4 * k + 1] = v.y; wf[4 * k + 2] = v.z; wf[4 * k + 3] = v.w; \
        } \
    }

template <int N> struct IC { static constexpr int value = N; };

__global__ void __launch_bounds__(512, 1)
k_chain(const __grid_constant__ CUtensorMap tmX, const __nv_bfloat16* __restrict__ mem0) {
    extern __shared__ uint8_t smem_raw[];
    uint32_t sb = (smem_u32(smem_raw) + 1023) & ~1023u;
    asm volatile("" : "+r"(sb));
    uint32_t g, h;
    asm volatile("mov.u32 %0, %cluster_ctarank;" : "=r"(g));
    asm volatile("mov.u32 %0, %clusterid.x;" : "=r"(h));
    g = __shfl_sync(0xffffffff, g, 0); h = __shfl_sync(0xffffffff, h, 0);
    const int warp = __shfl_sync(0xffffffff, threadIdx.x >> 5, 0);
    int lane = threadIdx.x & 31;
    asm volatile("" : "+r"(lane));
    {
        const uint32_t bar = sb + CH_BAR;
        if (threadIdx.x == 0) {
            for (int i = 0; i < 3; i++) mbar_init(bar + 8 * (B_X + i), 1);
            for (int i = 0; i < 2; i++) {
                mbar_init(bar + 8 * (B_S + i), 6);
                mbar_init(bar + 8 * (B_STGX + i), 8);
                mbar_init(bar + 8 * (B_STGF + i), 1);
                mbar_init(bar + 8 * (B_STGM + i), 6);
                for (int c = 0; c < CS; c++) mbar_init(bar + 8 * (B_MEM + i * 5 + c), c == (int)g ? 3 : 1);
            }
            mbar_init(bar + 8 * B_RED, 6);
            asm volatile("fence.mbarrier_init.release.cluster;" ::: "memory");
        }
    }
    __syncthreads();
    cluster_sync();
    if (threadIdx.x == 0) TL_MIN(2);
    pdl_wait();
    pdl_launch();
    if (threadIdx.x == 0) { TL_MIN(3); TL_MAX(4); }

    const int ntile = g < 4 ? 6 : 4;
    const int tile0 = 6 * g;
    const int lane_ = lane;
    const uint32_t sb_ = sb;
    if (warp < 12) {
        asm volatile("setmaxnreg.inc.sync.aligned.u32 160;");
        const bool isA = warp < 6;
        const int tl = isA ? warp : warp - 6;
        const bool valid = tl < ntile;
        const int tile = valid ? tile0 + tl : 0;
        LOAD_WEIGHTS()
        if (warp == 11) {
            uint32_t m = 0;
            #pragma unroll
            for (int i = 0; i < 16; i++) m = max(m, __ldcg(g_beta + i * 32 + lane));
            m = __reduce_max_sync(0xffffffff, m);
            if (lane == 0) sts32(sb + CH_EXP + 8, __float_as_uint(__uint_as_float(m) * 1.03f));
            #pragma unroll
            for (int i = 0; i < 2; i++) {
                const int sg = i * 32 + lane;
                uint32_t x = 0;
                #pragma unroll
                for (int k = 0; k < 6; k++) x = max(x, __ldcg(g_xmax + sg * 6 + k));
                sts32(sb + CH_XM + sg * 4, x);
            }
            __syncwarp();
        }
        auto xpart = [&](int sx) {
            OPAQUE_LOCALS
            const int xb = sx % 3;
            mbar_wait(bar + 8 * (B_X + xb), (sx / 3) & 1);
            float acc[16];
            const uint32_t xa = sb + CH_X + xb * 28672;
            { const int s = sx; (void)s; if (warp == 6) PROF(19); if (warp == 8) PROF(24); }
            wg_fence();
            #pragma unroll
            for (int k = 0; k < NKS; k++)
                wg_rs32(acc, wf[4 * k], wf[4 * k + 1], wf[4 * k + 2], wf[4 * k + 3], mkdesc(xa + (k >> 2) * 4096 + (k & 3) * 32, 16, 1024, 1), k != 0);
            wg_commit();
            wg_wait<0>();
            { const int s = sx; (void)s; if (warp == 6) PROF(21); if (warp == 8) PROF(25); }
            uint32_t vp[8];
            #pragma unroll
            for (int nu = 0; nu < 4; nu++) { vp[nu] = pack_bf16(acc[4 * nu], acc[4 * nu + 1]); vp[4 + nu] = pack_bf16(acc[4 * nu + 2], acc[4 * nu + 3]); }
            if (sx >= 2) mbar_wait(bar + 8 * (B_STGF + (sx & 1)), ((sx >> 1) - 1) & 1);
            const uint32_t sa = sb + CH_STGX + (sx & 1) * 8192 + (warp - 4) * 1024;
            const uint32_t stg_off = (lane & 7) * 64 + (((lane >> 3) ^ ((lane >> 1) & 3)) << 4);
            stsm_x4(sa + stg_off, vp[0], vp[1], vp[2], vp[3]);
            stsm_x4(sa + stg_off + 512, vp[4], vp[5], vp[6], vp[7]);
            __syncwarp();
            if (lane == 0) mbar_arrive(bar + 8 * (B_STGX + (sx & 1)));
        };
        if (threadIdx.x == 0) TL_MAX(5);
        if (warp >= 4) xpart(0);
        if (threadIdx.x == 128) TL_MAX(6);
        auto main_loop = [&](auto Gc) {
        constexpr int G = decltype(Gc)::value;
        for (int s = 0; s < NSEG; s++) {
            OPAQUE_LOCALS
            const int pb = s & 1, ph = (s >> 1) & 1;
            const uint32_t memt = sb + CH_MEM + pb * 7168;
            float d[4][4];
            #pragma unroll
            for (int i = 0; i < 4; i++) { d[i][0] = d[i][1] = d[i][2] = d[i][3] = 0.f; }
            if (!isA || s < NSEG - 1) { const uint32_t mb = memt + lane * 16, mbar0 = bar + 8 * (B_MEM + pb * 5); MEM_GEMM_BODY(mb, mbar0) }
            if (isA) {
                if (s < NSEG - 1) {
                    SCORES()
                    if (warp >= 4) mbar_wait(bar + 8 * B_RED, s & 1);
                }
            } else {
                #pragma unroll
                for (int i = 0; i < 4; i++) d[0][i] = (d[0][i] + d[1][i]) + (d[2][i] + d[3][i]);
                if (warp == 6) PROF(5);
                const uint32_t vm0 = pack_bf16(d[0][0], d[0][1]), vm1 = pack_bf16(d[0][2], d[0][3]);
                if (valid) {
                    uint32_t* dst = (uint32_t*)g_VM + ((size_t)(s * NH + h) * NTILE + tile) * 64 + lane;
                    dst[0] = vm0; dst[32] = vm1;
                }
                __syncwarp();
                if (lane == 0) mbar_arrive(bar + 8 * (B_STGM + pb));
                if (s < NSEG - 1) {
                    uint32_t vp[8];
                    {
                        const int row = (lane & 7) + (lane & 8);
                        const uint32_t va = sb + CH_STGX + pb * 8192 + (warp - 4) * 1024 + row * 64;
                        ldsm_x4(vp[0], vp[1], vp[2], vp[3], va + ((((lane >> 4)) ^ ((row >> 1) & 3)) << 4));
                        ldsm_x4(vp[4], vp[5], vp[6], vp[7], va + (((2 + (lane >> 4)) ^ ((row >> 1) & 3)) << 4));
                    }
                    if (warp == 11) {
                        uint32_t mxa = 0;
                        #pragma unroll
                        for (int u = 0; u < 14; u++) {
                            uint4 v;
                            asm volatile("ld.shared.v4.b32 {%0,%1,%2,%3}, [%4];" : "=r"(v.x), "=r"(v.y), "=r"(v.z), "=r"(v.w) : "r"(memt + u * 512 + lane * 16) : "memory");
                            mxa = __vmaxu2(mxa, __vmaxu2(__vmaxu2(v.x & 0x7FFF7FFFu, v.y & 0x7FFF7FFFu), __vmaxu2(v.z & 0x7FFF7FFFu, v.w & 0x7FFF7FFFu)));
                        }
                        uint32_t mb = max(mxa & 0xFFFFu, mxa >> 16) << 16, xm, bt;
                        asm volatile("ld.shared.b32 %0, [%1];" : "=r"(xm) : "r"(sb + CH_XM + s * 4) : "memory");
                        asm volatile("ld.shared.b32 %0, [%1];" : "=r"(bt) : "r"(sb + CH_EXP + 8) : "memory");
                        mb = max(__reduce_max_sync(0xffffffff, mb), xm);
                        const int eb = min(max((int)(__float_as_uint(__uint_as_float(mb) * __uint_as_float(bt)) >> 23) + 1, 30), 254);
                        if (lane == 0) sts32(sb + CH_EXP + pb * 4, (uint32_t)eb);
                    }
                    mbar_wait(bar + 8 * (B_S + pb), ph);
                    if (warp == 6) PROF(6);
                    const uint32_t ss = sb + CH_SS + lane * 8;
                    if (tl < 5) {
                        float2 v[5];
                        #pragma unroll
                        for (int c = 0; c < CS; c++) {
                            uint32_t hv;
                            asm volatile("ld.shared.b32 %0, [%1];" : "=r"(hv) : "r"(sb + CH_SB + pb * 3200 + (c * 5 + tl) * 128 + lane * 4) : "memory");
                            v[c] = __half22float2(*reinterpret_cast<__half2*>(&hv));
                        }
                        sts64(ss + tl * 256, (((v[0].x + v[1].x) + (v[2].x + v[3].x)) + v[4].x) * 64.0f, (((v[0].y + v[1].y) + (v[2].y + v[3].y)) + v[4].y) * 64.0f);
                    }
                    named_bar_sync(2, 192);
                    if (warp == 6) PROF(23);
                    float2 sv[5];
                    #pragma unroll
                    for (int nu = 0; nu < 5; nu++) sv[nu] = lds64(ss + nu * 256);
                    uint32_t eb;
                    asm volatile("ld.shared.b32 %0, [%1];" : "=r"(eb) : "r"(sb + CH_EXP + pb * 4) : "memory");
                    float mx = fmaxf(fmaxf(fmaxf(sv[0].x, sv[0].y), fmaxf(sv[1].x, sv[1].y)), fmaxf(fmaxf(sv[2].x, sv[2].y), fmaxf(sv[3].x, sv[3].y)));
                    mx = fmaxf(mx, fmaxf(sv[4].x, sv[4].y));
                    mx = fmaxf(mx, __shfl_xor_sync(0xffffffff, mx, 1));
                    mx = fmaxf(mx, __shfl_xor_sync(0xffffffff, mx, 2));
                    if (warp == 6) PROF(10);
                    uint32_t pf[5];
                    #pragma unroll
                    for (int nu = 0; nu < 5; nu++) pf[nu] = pack_bf16(ex2(sv[nu].x - mx), ex2(sv[nu].y - mx));
                    if (warp == 6) PROF(16);
                    float o0[4] = {0.f, 0.f, 0.f, 0.f}, o1[4] = {0.f, 0.f, 0.f, 0.f}, z0[4] = {0.f, 0.f, 0.f, 0.f};
                    constexpr uint32_t ONE2 = 0x3F803F80u;
                    hmma(z0, ONE2, ONE2, ONE2, ONE2, pf[0], pf[1]);
                    hmma(o0, vp[0], vp[1], vp[2], vp[3], pf[0], pf[1]);
                    hmma(o1, vp[4], vp[5], vp[6], vp[7], pf[2], pf[3]);
                    hmma(z0, ONE2, ONE2, ONE2, ONE2, pf[2], pf[3]);
                    hmma(o0, vm0, vm1, 0u, 0u, pf[4], 0u);
                    hmma(z0, ONE2, ONE2, ONE2, ONE2, pf[4], 0u);
                    const float qs = __uint_as_float((278u - eb) << 23);
                    const float f0 = qs * rcp_approx(z0[0]), f1 = qs * rcp_approx(z0[1]);
                    if (warp == 6) PROF(8);
                    if (valid) {
                        unsigned long long* r = g_R + ((size_t)(s & 3) * NCHUNK + 2 * tile) * 32 + lane;
                        #pragma unroll
                        for (int n = 0; n < 2; n++) {
                            const int q0 = min(max(__float2int_rn((o0[2 * n] + o1[2 * n]) * f0), -16777216), 16777215) + 16777216;
                            const int q1 = min(max(__float2int_rn((o0[2 * n + 1] + o1[2 * n + 1]) * f1), -16777216), 16777215) + 16777216;
                            const uint32_t lo = ((uint32_t)q1 << 5) + 1u, hi = (uint32_t)q0 << 2;
                            asm volatile("red.relaxed.gpu.global.add.u64 [%0], %1;" :: "l"(r + n * 32), "l"(((unsigned long long)hi << 32) | lo) : "memory");
                        }
                    }
                    if (warp == 6) PROF(9);
                    __syncwarp();
                    if (lane == 0) mbar_arrive(bar + 8 * B_RED);
                    if (warp == 6) PROF(7);
                    if (warp == 8) PROFG(26);
                    if (warp == 11) PROFG(27);
                }
            }
            if (s + 1 < NSEG && warp >= 4) {
                xpart(s + 1);
                if (warp == 6) PROF(11);
                if (warp == 8) PROF(12);
            }
        }
        };
        switch (g) {
            case 0: main_loop(IC<0>{}); break;
            case 1: main_loop(IC<1>{}); break;
            case 2: main_loop(IC<2>{}); break;
            case 3: main_loop(IC<3>{}); break;
            default: main_loop(IC<4>{}); break;
        }
    } else {
        asm volatile("setmaxnreg.dec.sync.aligned.u32 32;");
        const uint32_t bar = sb + CH_BAR;
        if (warp < 15) {
            const int pw = warp - 12;
            const int ch0 = 2 * tile0;
            const bool two = pw + 3 < ntile;
            auto arm_mem = [&](int pb) {
                for (int c = 1; c < CS; c++) { const int src = (g + c) % CS; mbar_expect_tx(bar + 8 * (B_MEM + pb * 5 + src), src < 4 ? 1536 : 1024); }
            };
            auto load_x = [&](int sx) {
                const int xb = sx % 3;
                mbar_expect_tx(bar + 8 * (B_X + xb), 28672);
                for (int bx = g; bx < 7; bx += CS)
                    tma_load_2d_mc(sb + CH_X + xb * 28672 + bx * 4096, &tmX, bx * 64, sx * SEG, bar + 8 * (B_X + xb), (uint16_t)((1 << CS) - 1));
            };
            if (pw == 2 && lane == 0) { load_x(0); load_x(1); load_x(2); }
            if (pw == 0 && lane == 0) arm_mem(0);
            for (int s = 0; s < NSEG; s++) {
                const int pb = s & 1;
                if (s > 0) mbar_wait(bar + 8 * B_RED, (s - 1) & 1);
                if (pw == 0 && lane == 0) {
                    if (s + 1 < NSEG) arm_mem(pb ^ 1);
                    if (s < NSEG - 1) mbar_expect_tx(bar + 8 * (B_S + pb), 4 * 640);
                }
                if (pw == 0) PROF(13);
                uint32_t val[4];
                uint32_t w[8];
                if (s == 0) {
                    #pragma unroll
                    for (int u = 0; u < 2; u++) {
                        const int col = (ch0 + 2 * (u == 0 || two ? pw + 3 * u : pw) + (lane >> 4)) * 8 + ((lane & 15) >> 1);
                        const unsigned short* m = (const unsigned short*)mem0 + (lane & 1) * 4 * DM + col;
                        val[2 * u] = (uint32_t)m[0] | ((uint32_t)m[DM] << 16);
                        val[2 * u + 1] = (uint32_t)m[2 * DM] | ((uint32_t)m[3 * DM] << 16);
                    }
                } else {
                    uint32_t eb;
                    asm volatile("ld.shared.b32 %0, [%1];" : "=r"(eb) : "r"(sb + CH_EXP + (pb ^ 1) * 4) : "memory");
                    const float is = __uint_as_float((eb - 24u) << 23);
                    const uint4* r0 = (const uint4*)(g_R + ((size_t)((s - 1) & 3) * NCHUNK + ch0 + 2 * pw) * 32) + lane;
                    const uint4* r1 = two ? r0 + 3 * 32 : r0;
                    { uint32_t t0, t1; asm volatile("mov.u32 %0, %clock;" : "=r"(t0)); do { asm volatile("mov.u32 %0, %clock;" : "=r"(t1)); } while (t1 - t0 < POLL_DELAY); }
                    int spin = 0;
                    bool ok;
                    do {
                        asm volatile("ld.relaxed.gpu.global.v4.u32 {%0,%1,%2,%3}, [%4];" : "=r"(w[0]), "=r"(w[1]), "=r"(w[2]), "=r"(w[3]) : "l"(r0) : "memory");
                        asm volatile("ld.relaxed.gpu.global.v4.u32 {%0,%1,%2,%3}, [%4];" : "=r"(w[4]), "=r"(w[5]), "=r"(w[6]), "=r"(w[7]) : "l"(r1) : "memory");
                        ok = __all_sync(0xffffffff, (((w[0] & w[2] & w[4] & w[6]) & 31u) == 16u) && (((w[0] | w[2] | w[4] | w[6]) & 31u) == 16u));
                        if (++spin > (1 << 22)) __trap();
                    } while (!ok);
                    #pragma unroll
                    for (int u = 0; u < 2; u++) {
                        float f[4];
                        #pragma unroll
                        for (int e = 0; e < 2; e++) {
                            const uint32_t lo = w[4 * u + 2 * e], hi = w[4 * u + 2 * e + 1];
                            f[2 * e] = (float)((int)(hi >> 2) - (1 << 28)) * is;
                            f[2 * e + 1] = (float)((int)(__funnelshift_r(lo, hi, 5) & 0x1FFFFFFFu) - (1 << 28)) * is;
                        }
                        val[2 * u] = pack_bf16(f[0], f[1]); val[2 * u + 1] = pack_bf16(f[2], f[3]);
                    }
                }
                if (pw == 0) PROF(14);
                if (pw == 1) PROFG(28);
                if (pw == 2) PROFG(29);
                const uint32_t off = CH_MEM + pb * 7168 + (ch0 + 2 * pw) * 128 + lane * 8, boff = CH_BAR + 8 * (B_MEM + pb * 5 + g);
                #pragma unroll
                for (int c = 1; c < CS; c++) {
                    const uint32_t rb = mapa(sb, (g + CS - c) % CS);
                    asm volatile("st.async.weak.shared::cluster.mbarrier::complete_tx::bytes.v2.b32 [%0], {%1,%2}, [%3];" :: "r"(rb + off), "r"(val[0]), "r"(val[1]), "r"(rb + boff) : "memory");
                    if (two) asm volatile("st.async.weak.shared::cluster.mbarrier::complete_tx::bytes.v2.b32 [%0], {%1,%2}, [%3];" :: "r"(rb + off + 768), "r"(val[2]), "r"(val[3]), "r"(rb + boff) : "memory");
                    if (c == 1) {
                        asm volatile("st.shared.v2.b32 [%0], {%1,%2};" :: "r"(sb + off), "r"(val[0]), "r"(val[1]) : "memory");
                        if (two) asm volatile("st.shared.v2.b32 [%0], {%1,%2};" :: "r"(sb + off + 768), "r"(val[2]), "r"(val[3]) : "memory");
                        __syncwarp();
                        if (lane == 0) mbar_arrive(sb + boff);
                    }
                }
                if (pw == 0) PROF(15);
                if (s >= 2 && pw == 1 && lane < ntile * 2) ((uint4*)(g_R + ((size_t)((s - 2) & 3) * NCHUNK + ch0) * 32))[h * ntile * 2 + lane] = make_uint4(0u, 0u, 0u, 0u);
                if (pw == 2 && lane == 0 && s >= 1 && s + 2 < NSEG) load_x(s + 2);
                if (h == 0) {
                    uint2* gm = (uint2*)(g_MEM + (s * NCHUNK + ch0 + 2 * pw) * 32) + lane;
                    gm[0] = make_uint2(val[0], val[1]);
                    if (two) gm[96] = make_uint2(val[2], val[3]);
                    __syncwarp();
                    if (lane == 0) red_release_add(&g_flags[2 * NSEG + s], 1);
                }
            }
        } else {
            for (int s = 0; s < NSEG; s++) {
                const int pb = s & 1;
                mbar_wait(bar + 8 * (B_STGX + pb), (s >> 1) & 1);
                #pragma unroll 2
                for (int t = 0; t < 8; t++) {
                    const int tl = t < 2 ? 4 + t : t - 2;
                    if (tl < ntile) {
                        uint4 e0, e1;
                        const uint32_t sa = sb + CH_STGX + pb * 8192 + t * 1024 + lane * 16;
                        asm volatile("ld.shared.v4.b32 {%0,%1,%2,%3}, [%4];" : "=r"(e0.x), "=r"(e0.y), "=r"(e0.z), "=r"(e0.w) : "r"(sa) : "memory");
                        asm volatile("ld.shared.v4.b32 {%0,%1,%2,%3}, [%4];" : "=r"(e1.x), "=r"(e1.y), "=r"(e1.z), "=r"(e1.w) : "r"(sa + 512) : "memory");
                        uint4* dst = (t < 2 ? g_TX : g_VX) + ((size_t)(s * NH + h) * NTILE + tile0 + tl) * 64 + lane;
                        dst[0] = e0; dst[32] = e1;
                    }
                }
                __syncwarp();
                if (lane == 0) {
                    mbar_arrive(bar + 8 * (B_STGF + pb));
                    asm volatile("fence.acq_rel.gpu;" ::: "memory");
                    asm volatile("red.relaxed.gpu.global.add.u32 [%0], %1;" :: "l"(&g_flags[s]), "r"(1u) : "memory");
                    mbar_wait(bar + 8 * (B_STGM + pb), (s >> 1) & 1);
                    asm volatile("fence.acq_rel.gpu;" ::: "memory");
                    asm volatile("red.relaxed.gpu.global.add.u32 [%0], %1;" :: "l"(&g_flags[5 * NSEG + s]), "r"(1u) : "memory");
                }
                __syncwarp();
            }
        }
    }
    __syncwarp();
    if (threadIdx.x == 0) TL_MAX(7);
    cluster_sync();
}

constexpr int TP_NST = 4;
constexpr int TP_X = 0;
constexpr int TP_STG = TP_NST * 28672;
constexpr int TP_BAR = TP_STG + 8192;
constexpr int NTP_UNITS = NH * CS;
#define TPS 4
constexpr int TP_SPLIT = TPS;
template <bool PROD>
DEVI void tproj_pass(uint32_t sb, int item, int& round, const CUtensorMap* tmX, int warp, int lane) {
    const uint32_t bar = sb + TP_BAR;
    constexpr int NS = NSEG / TP_SPLIT;
    const int pass = item % (NTP_UNITS / 2), s0 = (item / (NTP_UNITS / 2)) * NS;
    if constexpr (PROD) {
        if (warp == 8 && lane == 0) {
            for (int i = 0; i < NS; i++, round++) {
                const int st = round % TP_NST;
                if (round >= TP_NST) mbar_wait(bar + 32 + 8 * st, ((round / TP_NST) - 1) & 1);
                mbar_expect_tx(bar + 8 * st, 28672);
                for (int bx = 0; bx < 7; bx++) tma_load_2d(sb + TP_X + st * 28672 + bx * 4096, tmX, bx * 64, (s0 + i) * SEG, bar + 8 * st);
            }
        }
        return;
    }
    const int wg = warp >> 2, w = warp & 3;
    const int unit = 2 * pass + wg, h = unit / CS, tile = 6 * (unit % CS) + w;
    uint32_t wf[112];
    {
        const uint4* src = g_WF + ((size_t)(h * 2 * NTILE + tile) * NKS) * 32 + lane;
        #pragma unroll
        for (int k = 0; k < NKS; k++) { const uint4 v = __ldcg(src + k * 32); wf[4 * k] = v.x; wf[4 * k + 1] = v.y; wf[4 * k + 2] = v.z; wf[4 * k + 3] = v.w; }
    }
    const uint32_t sa = sb + TP_STG + warp * 1024;
    const uint32_t stg_off = (lane & 7) * 64 + (((lane >> 3) ^ ((lane >> 1) & 3)) << 4);
    for (int i = 0; i < NS; i++, round++) {
        const int st = round % TP_NST;
        mbar_wait(bar + 8 * st, (round / TP_NST) & 1);
        float acc[16];
        const uint32_t xa = sb + TP_X + st * 28672;
        wg_fence();
        #pragma unroll
        for (int k = 0; k < NKS; k++)
            wg_rs32(acc, wf[4 * k], wf[4 * k + 1], wf[4 * k + 2], wf[4 * k + 3], mkdesc(xa + (k >> 2) * 4096 + (k & 3) * 32, 16, 1024, 1), k != 0);
        wg_commit();
        wg_wait<0>();
        if ((threadIdx.x & 127) == 0) mbar_arrive(bar + 32 + 8 * st);
        uint32_t vp[8];
        #pragma unroll
        for (int nu = 0; nu < 4; nu++) { vp[nu] = pack_bf16(acc[4 * nu], acc[4 * nu + 1]); vp[4 + nu] = pack_bf16(acc[4 * nu + 2], acc[4 * nu + 3]); }
        stsm_x4(sa + stg_off, vp[0], vp[1], vp[2], vp[3]);
        stsm_x4(sa + stg_off + 512, vp[4], vp[5], vp[6], vp[7]);
        __syncwarp();
        uint4 e0, e1;
        asm volatile("ld.shared.v4.b32 {%0,%1,%2,%3}, [%4];" : "=r"(e0.x), "=r"(e0.y), "=r"(e0.z), "=r"(e0.w) : "r"(sa + lane * 16) : "memory");
        asm volatile("ld.shared.v4.b32 {%0,%1,%2,%3}, [%4];" : "=r"(e1.x), "=r"(e1.y), "=r"(e1.z), "=r"(e1.w) : "r"(sa + 512 + lane * 16) : "memory");
        uint4* dst = g_TX + ((size_t)((s0 + i) * NH + h) * NTILE + tile) * 64 + lane;
        dst[0] = e0; dst[32] = e1;
        __syncwarp();
    }
    named_bar_sync(1, 256);
    if (threadIdx.x == 0) red_release_add(&g_flags[4 * NSEG + s0 / NS], 1);
}

__device__ __align__(128) uint4 g_P[NSEG * NH * 192];
constexpr int XA_H = 0;
constexpr int XA_T = 71680;
constexpr int XA_S = XA_T + 2 * 57344;
constexpr int XO_V = 0;
constexpr int XO_VM = 131072;
constexpr int XO_P = XO_VM + 32768;
constexpr int XO_S = XO_P + 49152;
constexpr int XA_BAR = 225280;
static_assert(XA_T % 1024 == 0 && (XA_H + 35840) % 1024 == 0, "align");
#define FG_TARGET 15
#define XANP 14
constexpr int XA_NP = XANP;
constexpr int F_X = 0, F_G = 2 * NSEG, F_T = 4 * NSEG, F_P = NSEG;

DEVI void spin_flag(const unsigned int* p, unsigned int target) {
    long long t0 = clock64();
    while (ld_acquire(p) < target) { __nanosleep(32); if (clock64() - t0 > 8000000000LL) __trap(); }
}

template <bool PROD>
DEVI void xattn_cta(uint32_t sb, int first, int stride, const CUtensorMap* tmX, __nv_bfloat16* __restrict__ out, int warp, int lane) {
    const uint32_t bar = sb + XA_BAR;
    const bool isP = first < XA_NP;
    const int n0 = isP ? first : first - XA_NP, nstep = isP ? XA_NP : stride - XA_NP, nend = NSEG * 4;
    if constexpr (PROD) {
        if (warp == 8 && lane == 0) {
            int it = 0;
            for (int n = n0; n < nend; n += nstep, it++) {
                if (isP) {
                    const int s = n >> 2, j = n & 3, hb = it & 1;
                    if (it >= 2) mbar_wait(bar + 16 + 8 * hb, ((it >> 1) - 1) & 1);
                    mbar_expect_tx(bar + 8 * hb, 28672);
                    for (int bx = 0; bx < 7; bx++) tma_load_2d(sb + XA_H + hb * 35840 + bx * 5120, tmX, bx * 64, s * SEG, bar + 8 * hb);
                    spin_flag(&g_flags[F_X + s], NH * CS);
                    spin_flag(&g_flags[F_T + s / (NSEG / TP_SPLIT)], NTP_UNITS / 2);
                    fence_proxy_async_all();
                    for (int pr = 0; pr < 2; pr++) {
                        if (it >= 1) mbar_wait(bar + 48 + 8 * pr, (it - 1) & 1);
                        mbar_expect_tx(bar + 32 + 8 * pr, 57344);
                        bulk_load(sb + XA_T + pr * 57344, g_TX + (size_t)(s * NH + 4 * j + 2 * pr) * NTILE * 64, 57344, bar + 32 + 8 * pr);
                    }
                } else {
                    const int s = n >> 2, m = n & 3, nt = m < 3 ? 8 : 4;
                    if (it > 0) mbar_wait(bar + 8, (it - 1) & 1);
                    mbar_expect_tx(bar, NH * nt * (1024 + 256) + 49152);
                    spin_flag(&g_flags[F_X + s], NH * CS);
                    fence_proxy_async_all();
                    for (int h = 0; h < NH; h++) bulk_load(sb + XO_V + h * 8192, g_VX + ((size_t)(s * NH + h) * NTILE + 8 * m) * 64, nt * 1024, bar);
                    spin_flag(&g_flags[5 * NSEG + s], NH * CS);
                    fence_proxy_async_all();
                    for (int h = 0; h < NH; h++) bulk_load(sb + XO_VM + h * 2048, g_VM + ((size_t)(s * NH + h) * NTILE + 8 * m) * 16, nt * 256, bar);
                    spin_flag(&g_flags[F_P + s], 4);
                    fence_proxy_async_all();
                    bulk_load(sb + XO_P, g_P + (size_t)s * NH * 192, 49152, bar);
                }
            }
        }
        return;
    }
    const int wg = warp >> 2, w = warp & 3, tid = threadIdx.x;
    const int q = lane & 3, r = lane >> 2;
    int it = 0;
    for (int n = n0; n < nend; n += nstep, it++) {
        if (isP) {
            const int s = n >> 2, j = n & 3, hb = it & 1;
            const uint32_t ht = sb + XA_H + hb * 35840;
            if (tid == 0) spin_flag(&g_flags[F_G + s], FG_TARGET);
            named_bar_sync(1, 256);
            for (int i = tid; i < DM; i += 256) {
                const uint4 v = __ldcg((const uint4*)(g_MEM + s * NCHUNK * 32) + i);
                const uint32_t wv[4] = {v.x, v.y, v.z, v.w};
                const uint32_t a = ht + (i >> 6) * 5120 + 32 * 128 + (i & 7) * 2;
                #pragma unroll
                for (int row = 0; row < 8; row++) {
                    const unsigned short e = (unsigned short)(wv[row >> 1] >> ((row & 1) * 16));
                    asm volatile("st.shared.u16 [%0], %1;" :: "r"(a + row * 128 + ((((i >> 3) & 7) ^ row) << 4)), "h"(e) : "memory");
                }
            }
            fence_proxy_async();
            named_bar_sync(1, 256);
            mbar_wait(bar + 8 * hb, (it >> 1) & 1);
            mbar_wait(bar + 32 + 8 * wg, it & 1);
            float sc[20];
            #pragma unroll
            for (int i = 0; i < 20; i++) sc[i] = 0.f;
            wg_fence();
            #pragma unroll
            for (int kk = 0; kk < NKS; kk++)
                wg_ss40_mk(sc, mkdesc(sb + XA_T + wg * 57344 + kk * 1024, 28672, 512, 2), mkdesc(ht + (kk >> 2) * 5120 + (kk & 3) * 32, 16, 1024, 1), 1);
            wg_commit();
            wg_wait<0>();
            if ((tid & 127) == 0) { mbar_arrive(bar + 48 + 8 * wg); mbar_arrive(bar + 16 + 8 * hb); }
            uint32_t* pg = (uint32_t*)(g_P + (size_t)(s * NH + 4 * j + 2 * wg + (w >> 1)) * 192);
            #pragma unroll
            for (int half = 0; half < 2; half++) {
                const int tok = ((16 * w) & 31) + r + 8 * half;
                float mx = -3.0e38f;
                #pragma unroll
                for (int nu = 0; nu < 5; nu++)
                    #pragma unroll
                    for (int e = 0; e < 2; e++) {
                        float& v = sc[4 * nu + 2 * half + e];
                        if (nu < 4 && 8 * nu + 2 * q + e > tok) v = -3.0e38f;
                        mx = fmaxf(mx, v);
                    }
                mx = fmaxf(mx, __shfl_xor_sync(0xffffffff, mx, 1));
                mx = fmaxf(mx, __shfl_xor_sync(0xffffffff, mx, 2));
                float z = 0.f;
                #pragma unroll
                for (int nu = 0; nu < 5; nu++)
                    #pragma unroll
                    for (int e = 0; e < 2; e++) { float& v = sc[4 * nu + 2 * half + e]; v = ex2(v - mx); z += v; }
                z += __shfl_xor_sync(0xffffffff, z, 1);
                z += __shfl_xor_sync(0xffffffff, z, 2);
                const float zi = __fdividef(1.0f, z);
                uint32_t* pa = pg + (tok >> 3) * 192 + (tok & 7) * 4 + q;
                #pragma unroll
                for (int nu = 0; nu < 5; nu++) pa[nu * 32] = pack_bf16(sc[4 * nu + 2 * half] * zi, sc[4 * nu + 2 * half + 1] * zi);
                pa[5 * 32] = 0u;
            }
            named_bar_sync(1, 256);
            if (tid == 0) red_release_add(&g_flags[F_P + s], 1);
        } else {
            const int s = n >> 2, m = n & 3;
            const bool act = m < 3 || wg == 0;
            mbar_wait(bar, it & 1);
            float o[16];
            #pragma unroll
            for (int i = 0; i < 16; i++) o[i] = 0.f;
            wg_fence();
            #pragma unroll
            for (int h = 0; h < NH; h++) {
                const uint32_t va = sb + XO_V + h * 8192 + wg * 4096, vm = sb + XO_VM + h * 2048 + wg * 1024, pa = sb + XO_P + h * 3072;
                wg_ss32_kk(o, mkdesc(va, 16, 512, 2), mkdesc(pa, 128, 768, 0), 1);
                wg_ss32_kk(o, mkdesc(va + 32, 16, 512, 2), mkdesc(pa + 256, 128, 768, 0), 1);
                wg_ss32_kk(o, mkdesc(vm, 0, 128, 0), mkdesc(pa + 512, 128, 768, 0), 1);
            }
            wg_commit();
            wg_wait<0>();
            named_bar_sync(1, 256);
            if (tid == 0) mbar_arrive(bar + 8);
            if (act) {
                const uint32_t so = sb + XO_S + wg * 4608;
                uint32_t p[8];
                #pragma unroll
                for (int nu = 0; nu < 4; nu++) { p[nu] = pack_bf16(o[4 * nu], o[4 * nu + 1]); p[4 + nu] = pack_bf16(o[4 * nu + 2], o[4 * nu + 3]); }
                const uint32_t a = so + lane * 144 + w * 32;
                stsm_x4_t(a, p[0], p[1], p[2], p[3]);
                stsm_x4_t(a + 16, p[4], p[5], p[6], p[7]);
                named_bar_sync(2 + wg, 128);
                #pragma unroll
                for (int i = 0; i < 2; i++) {
                    const int idx = i * 128 + (tid & 127), tok = idx >> 3, ch = idx & 7;
                    uint4 v;
                    asm volatile("ld.shared.v4.b32 {%0,%1,%2,%3}, [%4];" : "=r"(v.x), "=r"(v.y), "=r"(v.z), "=r"(v.w) : "r"(so + tok * 144 + ch * 16) : "memory");
                    *(uint4*)(out + (size_t)(s * SEG + tok) * OUTW + m * 128 + wg * 64 + ch * 8) = v;
                }
                named_bar_sync(2 + wg, 128);
            }
        }
    }
}

constexpr int NB_CTA = 16;
__device__ __align__(128) __nv_bfloat16 g_PQ[SEQ * 512];
__device__ __align__(128) __nv_bfloat16 g_PK[SEQ * 512];
__device__ __align__(128) __nv_bfloat16 g_VV[SEQ * 512];
constexpr int LB_X = 0;
constexpr int LB_ST = 131072;
constexpr int LB_BAR = 229376;

DEVI float phi_f(float t) { return (t > 0.f ? t + 1.0f : __expf(t)) + 1e-6f; }
DEVI float bf16r(float x) { return __bfloat162float(__float2bfloat16_rn(x)); }

template <bool PROD>
DEVI void lin_cta(uint32_t sb, int tile, const CUtensorMap* tmXb, const CUtensorMap* tmW, const CUtensorMap* tmWo, const CUtensorMap* tmPQ,
                  const CUtensorMap* tmPK, const CUtensorMap* tmVV, __nv_bfloat16* __restrict__ out, int warp, int lane) {
    const uint32_t bar = sb + LB_BAR;
    const uint32_t bX = bar, bFull = bar + 8, bEmpty = bar + 40, bF2 = bar + 72, bE2 = bar + 88, bPQ = bar + 104, bGo = bar + 112;
    const int row0 = tile * 128;
    unsigned int* cntB = &g_flags[3 * NSEG];
    constexpr int NS1 = 4;
    if constexpr (PROD) {
        if (warp == 8 && lane == 0) {
            mbar_expect_tx(bX, 114688);
            for (int bx = 0; bx < 7; bx++) tma_load_2d(sb + LB_X + bx * 16384, tmXb, bx * 64, row0, bX);
            for (int it = 0; it < 49; it++) {
                const int st = it % NS1, nc = it / 7, kc = it % 7;
                if (it >= NS1) mbar_wait(bEmpty + 8 * st, ((it / NS1) - 1) & 1);
                mbar_expect_tx(bFull + 8 * st, 24576);
                for (int a = 0; a < 3; a++) tma_load_2d(sb + LB_ST + st * 24576 + a * 8192, tmW, nc * 192 + a * 64, kc * 64, bFull + 8 * st);
            }
            mbar_wait(bGo, 0);
            fence_proxy_async_all();
            for (int rho = 0; rho < 4; rho++) {
                const int st = rho & 1;
                if (rho >= 2) mbar_wait(bE2 + 8 * st, 0);
                mbar_expect_tx(bF2 + 8 * st, 65536);
                for (int a = 0; a < 2; a++) {
                    tma_load_2d(sb + st * 65536 + a * 16384, tmPK, (2 * rho + a) * 64, row0, bF2 + 8 * st);
                    tma_load_2d(sb + st * 65536 + 32768 + a * 16384, tmVV, (2 * rho + a) * 64, row0, bF2 + 8 * st);
                }
            }
            mbar_wait(bE2, 1); mbar_wait(bE2 + 8, 1);
            mbar_expect_tx(bPQ, 131072);
            for (int bx = 0; bx < 8; bx++) tma_load_2d(sb + bx * 16384, tmPQ, bx * 64, row0, bPQ);
            for (int it = 0; it < 16; it++) {
                const int st = it & 1, pass = it >> 3, hp = it & 7, na = pass == 0 ? 4 : 3;
                if (it >= 2) mbar_wait(bEmpty + 8 * st, (((49 + 3 - st) / NS1) + ((it >> 1) - 1)) & 1);
                else mbar_wait(bEmpty + 8 * st, (((49 + 3 - st) / NS1) - 1) & 1);
                mbar_expect_tx(bFull + 8 * st, na * 2 * 4096);
                for (int hh = 0; hh < 2; hh++)
                    for (int a = 0; a < na; a++)
                        tma_load_2d(sb + LB_ST + st * 32768 + hh * 16384 + a * 4096, tmWo, pass * 256 + a * 64, (2 * hp + hh) * 28, bFull + 8 * st);
            }
        }
        return;
    }
    const int wg = warp >> 2, w = warp & 3, tid = threadIdx.x, q = lane & 3, r = lane >> 2;
    for (int i = tid; i < 128 * NH; i += 256) {
        const size_t o = (size_t)(row0 + (i >> 4)) * 512 + (i & 15) * 32 + 28;
        *(uint2*)(g_PQ + o) = make_uint2(0u, 0u);
        *(uint2*)(g_PK + o) = make_uint2(0u, 0u);
        *(uint2*)(g_VV + o) = make_uint2(0x00003F80u, 0u);
    }
    mbar_wait(bX, 0);
    {
        float acc[96];
        for (int nc = 0; nc < 7; nc++) {
            for (int kc = 0; kc < 7; kc++) {
                const int it = nc * 7 + kc, st = it % NS1;
                mbar_wait(bFull + 8 * st, (it / NS1) & 1);
                wg_fence();
                #pragma unroll
                for (int ks = 0; ks < 4; ks++)
                    wg_ss192_kn(acc, mkdesc(sb + LB_X + kc * 16384 + wg * 8192 + ks * 32, 16, 1024, 1), mkdesc(sb + LB_ST + st * 24576 + ks * 2048, 8192, 1024, 1), (kc | ks) != 0);
                wg_commit();
                wg_wait<0>();
                if (tid % 128 == 0) mbar_arrive(bEmpty + 8 * st);
            }
            #pragma unroll
            for (int j = 0; j < 24; j++) {
                const int n = nc * 192 + 8 * j + 2 * q;
                const int part = n / 448, m = n - part * 448, hh = m / 28, d = m - hh * 28;
                __nv_bfloat16* dst = (part == 0 ? g_PQ : (part == 1 ? g_PK : g_VV)) + (size_t)(row0 + wg * 64 + w * 16 + r) * 512 + hh * 32 + d;
                #pragma unroll
                for (int half = 0; half < 2; half++) {
                    float a = bf16r(acc[4 * j + 2 * half]), b = bf16r(acc[4 * j + 2 * half + 1]);
                    if (part < 2) { a = phi_f(a); b = phi_f(b); }
                    *(uint32_t*)(dst + half * 8 * 512) = pack_bf16(a, b);
                }
            }
        }
    }
    __threadfence();
    fence_proxy_async_all();
    named_bar_sync(1, 256);
    if (tid == 0) mbar_arrive(bGo);
    for (int rho = 0; rho < 4; rho++) {
        const int st = rho & 1;
        mbar_wait(bF2 + 8 * st, rho >> 1);
        float kv[32];
        wg_fence();
        #pragma unroll
        for (int ks = 0; ks < 8; ks++)
            wg_ss64_mn(kv, mkdesc(sb + st * 65536 + wg * 16384 + ks * 2048, 16384, 1024, 1), mkdesc(sb + st * 65536 + 32768 + wg * 16384 + ks * 2048, 16384, 1024, 1), ks != 0);
        wg_commit();
        wg_wait<0>();
        if (tid % 128 == 0) mbar_arrive(bE2 + 8 * st);
        const int hh = 4 * rho + 2 * wg + (w >> 1);
        float* dst = g_KV + (hh * 32 + (w & 1) * 16 + r) * 32 + 2 * q;
        #pragma unroll
        for (int j = 0; j < 4; j++) {
            const float a0 = (w >> 1) ? kv[16 + 4 * j] : kv[4 * j], a1 = (w >> 1) ? kv[17 + 4 * j] : kv[4 * j + 1];
            const float a2 = (w >> 1) ? kv[18 + 4 * j] : kv[4 * j + 2], a3 = (w >> 1) ? kv[19 + 4 * j] : kv[4 * j + 3];
            atomicAdd(dst + 8 * j, a0); atomicAdd(dst + 8 * j + 1, a1);
            atomicAdd(dst + 256 + 8 * j, a2); atomicAdd(dst + 256 + 8 * j + 1, a3);
        }
    }
    __threadfence();
    named_bar_sync(1, 256);
    if (tid == 0) { red_release_add(cntB, 1); spin_flag(cntB, NB_CTA); }
    named_bar_sync(1, 256);
    const uint32_t kvt = sb + 196608;
    for (int i = tid; i < NH * 32 * 16; i += 256) {
        const int hh = i >> 9, e = (i >> 4) & 31, d2 = (i & 15) * 2;
        const float a = __ldcg(g_KV + (hh * 32 + d2) * 32 + e), b = __ldcg(g_KV + (hh * 32 + d2 + 1) * 32 + e);
        sts32(kvt + hh * 2048 + (e >> 3) * 512 + (d2 >> 3) * 128 + (e & 7) * 16 + (d2 & 7) * 2, pack_bf16(a, b));
    }
    fence_proxy_async();
    named_bar_sync(1, 256);
    mbar_wait(bPQ, 0);
    for (int hh = 0; hh < NH; hh++) {
        float nm[16];
        const uint32_t pa = sb + (hh >> 1) * 16384 + wg * 8192 + (hh & 1) * 64;
        wg_fence();
        wg_ss32_kk(nm, mkdesc(pa, 16, 1024, 1), mkdesc(kvt + hh * 2048, 128, 512, 0), 0);
        wg_ss32_kk(nm, mkdesc(pa + 32, 16, 1024, 1), mkdesc(kvt + hh * 2048 + 256, 128, 512, 0), 1);
        wg_commit();
        wg_wait<0>();
        #pragma unroll
        for (int half = 0; half < 2; half++) {
            const float den = __shfl_sync(0xffffffff, nm[12 + 2 * half], (lane & ~3) | 2) + 1e-6f;
            const float di = 1.0f / den;
            const int row = wg * 64 + w * 16 + r + 8 * half;
            #pragma unroll
            for (int j = 0; j < 4; j++) {
                const bool pad = (j == 3) && (q >= 2);
                const uint32_t v = pad ? 0u : pack_bf16(nm[4 * j + 2 * half] * di, nm[4 * j + 2 * half + 1] * di);
                const int chunk = (hh & 1) * 4 + j;
                sts32(sb + (hh >> 1) * 16384 + row * 128 + ((chunk ^ (row & 7)) << 4) + q * 4, v);
            }
        }
    }
    fence_proxy_async();
    named_bar_sync(1 + 1 + wg, 128);
    int it = 0;
    #pragma unroll 1
    for (int pass = 0; pass < 2; pass++) {
        float acc[128];
        for (int hp = 0; hp < 8; hp++, it++) {
            const int st = it & 1;
            mbar_wait(bFull + 8 * st, (((49 + 3 - st) / NS1) + (it >> 1)) & 1);
            wg_fence();
            #pragma unroll
            for (int ks = 0; ks < 4; ks++) {
                const uint64_t da = mkdesc(sb + hp * 16384 + wg * 8192 + ks * 32, 16, 1024, 1);
                const uint64_t db = mkdesc(sb + LB_ST + st * 32768 + (ks >> 1) * 16384 + (ks & 1) * 2048, 4096, 1024, 1);
                if (pass == 0) wg_ss256_kn(acc, da, db, (hp | ks) != 0); else wg_ss192_kn(acc, da, db, (hp | ks) != 0);
            }
            wg_commit();
            wg_wait<0>();
            if (tid % 128 == 0) mbar_arrive(bEmpty + 8 * st);
        }
        const int nj = pass == 0 ? 32 : 24;
        #pragma unroll
        for (int j = 0; j < 32; j++) {
            if (j < nj) {
                __nv_bfloat16* dst = out + (size_t)(row0 + wg * 64 + w * 16 + r) * OUTW + DM + pass * 256 + 8 * j + 2 * q;
                *(uint32_t*)dst = pack_bf16(acc[4 * j], acc[4 * j + 1]);
                *(uint32_t*)(dst + 8 * OUTW) = pack_bf16(acc[4 * j + 2], acc[4 * j + 3]);
            }
        }
    }
}

constexpr int AUX_SMEM = 229376 + 256 + 1024;
constexpr int AUX_GRID = 52;
__global__ void __launch_bounds__(384, 1)
k_aux(const __grid_constant__ CUtensorMap tmX, const __grid_constant__ CUtensorMap tmXb, const __grid_constant__ CUtensorMap tmW,
      const __grid_constant__ CUtensorMap tmWo, const __grid_constant__ CUtensorMap tmPQ, const __grid_constant__ CUtensorMap tmPK,
      const __grid_constant__ CUtensorMap tmVV, __nv_bfloat16* __restrict__ out, const int nb_cta) {
    extern __shared__ uint8_t smem_raw[];
    const uint32_t sb = (smem_u32(smem_raw) + 1023) & ~1023u;
    const int warp = __shfl_sync(0xffffffff, threadIdx.x >> 5, 0), lane = threadIdx.x & 31;
    const bool isB = (int)blockIdx.x < nb_cta;
    if (threadIdx.x == 0) {
        if (isB) {
            const uint32_t bar = sb + LB_BAR;
            mbar_init(bar, 1);
            for (int i = 0; i < 4; i++) { mbar_init(bar + 8 + 8 * i, 1); mbar_init(bar + 40 + 8 * i, 2); }
            for (int i = 0; i < 2; i++) { mbar_init(bar + 72 + 8 * i, 1); mbar_init(bar + 88 + 8 * i, 2); }
            mbar_init(bar + 104, 1); mbar_init(bar + 112, 1);
        } else {
            const uint32_t tb = sb + TP_BAR;
            for (int i = 0; i < TP_NST; i++) { mbar_init(tb + 8 * i, 1); mbar_init(tb + 32 + 8 * i, 2); }
        }
        asm volatile("fence.mbarrier_init.release.cluster;" ::: "memory");
    }
    __syncthreads();
    if (threadIdx.x == 0) TL_MIN(8);
    #define AUX_BODY(PROD) \
        if (isB) lin_cta<PROD>(sb, blockIdx.x, &tmXb, &tmW, &tmWo, &tmPQ, &tmPK, &tmVV, out, warp, lane); \
        else { \
            int round = 0; \
            for (int pass = blockIdx.x - nb_cta; pass < TP_SPLIT * (NTP_UNITS / 2); pass += gridDim.x - nb_cta) tproj_pass<PROD>(sb, pass, round, &tmX, warp, lane); \
            if (threadIdx.x == 0) TL_MAX(11); \
            named_bar_sync(15, 384);        \
            if (threadIdx.x == 0) { \
                const uint32_t bar = sb + XA_BAR; \
                if ((int)blockIdx.x - nb_cta < XA_NP) { mbar_init(bar, 1); mbar_init(bar + 8, 1); mbar_init(bar + 16, 2); mbar_init(bar + 24, 2); mbar_init(bar + 32, 1); mbar_init(bar + 40, 1); mbar_init(bar + 48, 1); mbar_init(bar + 56, 1); } \
                else { mbar_init(bar, 1); mbar_init(bar + 8, 1); } \
                asm volatile("fence.mbarrier_init.release.cluster;" ::: "memory"); \
            } \
            named_bar_sync(15, 384); \
            xattn_cta<PROD>(sb, blockIdx.x - nb_cta, gridDim.x - nb_cta, &tmX, out, warp, lane); \
        }
    if (warp >= 8) {
        asm volatile("setmaxnreg.dec.sync.aligned.u32 40;");
        AUX_BODY(true)
    } else {
        asm volatile("setmaxnreg.inc.sync.aligned.u32 232;");
        AUX_BODY(false)
        if (threadIdx.x == 0) { if (isB) TL_MAX(9); else TL_MAX(10); }
    }
}

typedef CUresult (*PFN_encodeTiled)(CUtensorMap*, CUtensorMapDataType, cuuint32_t, void*, const cuuint64_t*, const cuuint64_t*,
                                    const cuuint32_t*, const cuuint32_t*, CUtensorMapInterleave, CUtensorMapSwizzle,
                                    CUtensorMapL2promotion, CUtensorMapFloatOOBfill);
static PFN_encodeTiled s_encode = nullptr;

static CUtensorMap make_map(const void* ptr, uint64_t cols, uint64_t rows, uint32_t box_cols, uint32_t box_rows, CUtensorMapSwizzle swz) {
    CUtensorMap m;
    cuuint64_t dims[2] = {cols, rows};
    cuuint64_t strides[1] = {cols * 2};
    cuuint32_t box[2] = {box_cols, box_rows};
    cuuint32_t es[2] = {1, 1};
    s_encode(&m, CU_TENSOR_MAP_DATA_TYPE_BFLOAT16, 2, const_cast<void*>(ptr), dims, strides, box, es, CU_TENSOR_MAP_INTERLEAVE_NONE, swz,
             CU_TENSOR_MAP_L2_PROMOTION_L2_256B, CU_TENSOR_MAP_FLOAT_OOB_FILL_NONE);
    return m;
}

extern "C" void kernel_launch(void* const* d_in, const int* in_sizes, int n_in, void* d_out, int out_size) {
    (void)in_sizes; (void)n_in; (void)out_size;
    const __nv_bfloat16* A_x = (const __nv_bfloat16*)d_in[0];
    const __nv_bfloat16* A_mem0 = (const __nv_bfloat16*)d_in[1];
    const __nv_bfloat16* A_Wq = (const __nv_bfloat16*)d_in[2];
    const __nv_bfloat16* A_Wk = (const __nv_bfloat16*)d_in[3];
    const __nv_bfloat16* A_Wv = (const __nv_bfloat16*)d_in[4];
    const __nv_bfloat16* A_Wo = (const __nv_bfloat16*)d_in[5];
    const __nv_bfloat16* B_x = (const __nv_bfloat16*)d_in[7];
    const __nv_bfloat16* B_wqkv = (const __nv_bfloat16*)d_in[8];
    const __nv_bfloat16* B_wo = (const __nv_bfloat16*)d_in[9];
    __nv_bfloat16* out = (__nv_bfloat16*)d_out;
    static bool init = false;
    if (!init) {
        void* fn = nullptr;
        cudaDriverEntryPointQueryResult qr;
        cudaGetDriverEntryPoint("cuTensorMapEncodeTiled", &fn, cudaEnableDefault, &qr);
        s_encode = (PFN_encodeTiled)fn;
        cudaFuncSetAttribute(k_prep, cudaFuncAttributeMaxDynamicSharedMemorySize, PREP_SMEM);
        cudaFuncSetAttribute(k_chain, cudaFuncAttributeMaxDynamicSharedMemorySize, CH_SMEM);
        cudaFuncSetAttribute(k_aux, cudaFuncAttributeMaxDynamicSharedMemorySize, AUX_SMEM);

        init = true;
    }
    const CUtensorMap tmWq = make_map(A_Wq, NH * DH, DM, 64, 224, CU_TENSOR_MAP_SWIZZLE_128B);
    const CUtensorMap tmWv = make_map(A_Wv, NH * DH, DM, 64, 224, CU_TENSOR_MAP_SWIZZLE_128B);
    const CUtensorMap tmWk = make_map(A_Wk, NH * DH, DM, 64, 128, CU_TENSOR_MAP_SWIZZLE_128B);
    const CUtensorMap tmWo = make_map(A_Wo, DM, NH * DH, 64, 256, CU_TENSOR_MAP_SWIZZLE_128B);
    const CUtensorMap tmX = make_map(A_x, DM, SEQ, 64, 32, CU_TENSOR_MAP_SWIZZLE_128B);
    cudaStream_t st = cudaStreamPerThread;

    k_prep<<<128, 384, PREP_SMEM, st>>>(tmWq, tmWk, tmWv, tmWo, A_x);
    {
        cudaLaunchConfig_t cfg = {};
        cfg.gridDim = dim3(NH * CS); cfg.blockDim = dim3(512); cfg.dynamicSmemBytes = CH_SMEM; cfg.stream = st;
        cudaLaunchAttribute at[2];
        at[0].id = cudaLaunchAttributeClusterDimension; at[0].val.clusterDim.x = CS; at[0].val.clusterDim.y = 1; at[0].val.clusterDim.z = 1;
        at[1].id = cudaLaunchAttributeProgrammaticStreamSerialization; at[1].val.programmaticStreamSerializationAllowed = 1;
        cfg.attrs = at; cfg.numAttrs = 2;
        cudaLaunchKernelEx(&cfg, k_chain, tmX, A_mem0);
    }
        {
        void *pPQ, *pPK, *pVV;
        cudaGetSymbolAddress(&pPQ, g_PQ); cudaGetSymbolAddress(&pPK, g_PK); cudaGetSymbolAddress(&pVV, g_VV);
        const CUtensorMap tmXb = make_map(B_x, DM, SEQ, 64, 128, CU_TENSOR_MAP_SWIZZLE_128B);
        const CUtensorMap tmW = make_map(B_wqkv, 3 * DM, DM, 64, 64, CU_TENSOR_MAP_SWIZZLE_128B);
        const CUtensorMap tmWo2 = make_map(B_wo, DM, DM, 64, 32, CU_TENSOR_MAP_SWIZZLE_128B);
        const CUtensorMap tmPQ = make_map(pPQ, 512, SEQ, 64, 128, CU_TENSOR_MAP_SWIZZLE_128B);
        const CUtensorMap tmPK = make_map(pPK, 512, SEQ, 64, 128, CU_TENSOR_MAP_SWIZZLE_128B);
        const CUtensorMap tmVV = make_map(pVV, 512, SEQ, 64, 128, CU_TENSOR_MAP_SWIZZLE_128B);
        cudaLaunchConfig_t cfg = {};
        cfg.gridDim = dim3(AUX_GRID); cfg.blockDim = dim3(384); cfg.dynamicSmemBytes = AUX_SMEM; cfg.stream = st;
        cudaLaunchAttribute at[1];
        at[0].id = cudaLaunchAttributeProgrammaticStreamSerialization; at[0].val.programmaticStreamSerializationAllowed = 1;
        cfg.attrs = at; cfg.numAttrs = 1;
        cudaLaunchKernelEx(&cfg, k_aux, tmX, tmXb, tmW, tmWo2, tmPQ, tmPK, tmVV, out, NB_CTA);
    }

}
```
